```python
import torch

def _softmax(x, axis=-1):
    return torch.softmax(x, dim=axis)
def _gelu(x):
    return torch.nn.functional.gelu(x, approximate="tanh")
def _silu(x):
    return torch.nn.functional.silu(x)
def _sigmoid(x):
    return torch.sigmoid(x)
def _layernorm(x, axis=-1, eps=1e-5):
    m = x.mean(dim=axis, keepdim=True)
    v = x.var(dim=axis, keepdim=True, unbiased=False)
    return (x - m) / torch.sqrt(v + eps)
def _scatter_add(tgt, idx, src, axis=0):
    return tgt.clone().index_add_(axis, idx, src)
def _segment_sum(src, seg, n):
    out = torch.zeros((n,) + src.shape[1:], dtype=src.dtype)
    return out.index_add_(0, seg, src)
def _pad(x, pw):
    flat = tuple(v for pair in reversed(pw) for v in pair)
    return torch.nn.functional.pad(x, flat)

kernel_name = 'sequential_preLN__ssm_conv_h3__glu_gated_glu__prompt'

def setup_inputs():

    _w = (lambda a: (lambda t: t.to(torch.bfloat16) if t.is_floating_point() else t)(torch.as_tensor(a)))
    def _A_setup():
        B, S, D = 1, 2048, 512
        ks = 4
        return {
            "q": _w((lambda *s: torch.randn(*s, dtype=torch.bfloat16) * 0.05)(B, S, D)),
            "k": _w((lambda *s: torch.randn(*s, dtype=torch.bfloat16) * 0.4)(B, S, D)),
            "v": _w((lambda *s: torch.randn(*s, dtype=torch.bfloat16) * 0.4)(B, S, D)),
            "shift_k": _w((lambda *s: torch.randn(*s, dtype=torch.bfloat16) * 0.4)(D, ks) * 0.5),
            "ssm_k": _w((lambda *s: torch.randn(*s, dtype=torch.bfloat16) * 0.4)(D, S) * (1.0 / S ** 0.5)),
            "ssm_D": _w((lambda *s: torch.randn(*s, dtype=torch.bfloat16) * 0.4)(D)),
        }
    _A_in = _A_setup()

    def _B_setup():
        B, S, D, F = 1, 2048, 512, 1792
        return {
            "x": _w((lambda *s: torch.randn(*s, dtype=torch.bfloat16) * 0.05)(B, S, D)),
            "w_gate": _w((lambda *s: torch.randn(*s, dtype=torch.bfloat16) * 0.05)(D, F)),
            "w_up": _w((lambda *s: torch.randn(*s, dtype=torch.bfloat16) * 0.05)(D, F)),
            "w_down": _w((lambda *s: torch.randn(*s, dtype=torch.bfloat16) * 0.05)(F, D)),
        }
    _B_in = _B_setup()

    return {
        "A_q": _A_in["q"],
        "A_k": _A_in["k"],
        "A_v": _A_in["v"],
        "A_shift_k": _A_in["shift_k"],
        "A_ssm_k": _A_in["ssm_k"],
        "A_ssm_D": _A_in["ssm_D"],
        "B_x": _B_in["x"],
        "B_w_gate": _B_in["w_gate"],
        "B_w_up": _B_in["w_up"],
        "B_w_down": _B_in["w_down"],
    }

def reference(A_q, A_k, A_v, A_shift_k, A_ssm_k, A_ssm_D, B_x, B_w_gate, B_w_up, B_w_down):
    def _A_ref(q, k, v, shift_k, ssm_k, ssm_D):
        B, S, D = q.shape
        ks = shift_k.shape[-1]
        k_pad = _pad(k, ((0, 0), (ks - 1, 0), (0, 0)))
        k_shift = torch.zeros_like(k)
        for t in range(ks):
            k_shift = k_shift + k_pad[:, t:t + S, :] * shift_k[:, ks - 1 - t][None, None, :]
        kv = k_shift * v
        L = 2 * S
        kv_pad = _pad(kv, ((0, 0), (0, S), (0, 0)))
        kf_pad = _pad(ssm_k, ((0, 0), (0, S)))
        kv_f = (lambda x, axes=(-2,-1): torch.fft.rfft2(x.float(), dim=axes))(kv_pad[:, None, :, :], axes=(1, 2))
        kf_f = (lambda x, axes=(-2,-1): torch.fft.rfft2(x.float(), dim=axes))(kf_pad[:, None, :], axes=(1, 2))
        kf_f = (lambda x, *d: x.permute(*d))(kf_f, 1, 2, 0)
        y_f = kv_f * kf_f[None, :, :, :]
        y = (lambda x, s, axes=(-2,-1): torch.fft.irfft2(x, s=s, dim=axes).to(torch.bfloat16))(y_f, (1, L), axes=(1, 2))[:, 0, :S, :]
        y = y + kv * ssm_D[None, None, :]
        return q * y

    def _B_ref(x, w_gate, w_up, w_down):
        g = torch.einsum("bsd,df->bsf", x, w_gate)
        u = torch.einsum("bsd,df->bsf", x, w_up)
        h = _sigmoid(g) * u
        return torch.einsum("bsf,fd->bsd", h, w_down)

    x = A_q
    h = x + _A_ref(_layernorm(x, axis=-1), A_k, A_v, A_shift_k, A_ssm_k, A_ssm_D)
    h2 = h + _B_ref(_layernorm(h, axis=-1), B_w_gate, B_w_up, B_w_down)
    return h2
```

```cpp
#include <cuda_runtime.h>
#include <cuda_bf16.h>
#include <cuda.h>
#include <stdint.h>

typedef __nv_bfloat16 bf16;
typedef __nv_bfloat162 bf162;

constexpr int S_ = 2048, D_ = 512, F_ = 1792;

__device__ bf16 g_z[S_ * D_];
__device__ bf16 g_h[S_ * D_];
__device__ bf16 g_hh[S_ * F_];

__device__ __forceinline__ uint32_t smem_u32(const void* p) { return (uint32_t)__cvta_generic_to_shared(p); }

__device__ __forceinline__ void mbar_init(uint32_t bar, uint32_t count) {
    asm volatile("mbarrier.init.shared::cta.b64 [%0], %1;" ::"r"(bar), "r"(count) : "memory");
}
__device__ __forceinline__ void mbar_expect_tx(uint32_t bar, uint32_t bytes) {
    asm volatile("mbarrier.arrive.expect_tx.shared::cta.b64 _, [%0], %1;" ::"r"(bar), "r"(bytes) : "memory");
}
__device__ __forceinline__ void mbar_arrive(uint32_t bar) {
    asm volatile("mbarrier.arrive.shared::cta.b64 _, [%0];" ::"r"(bar) : "memory");
}
__device__ __forceinline__ bool mbar_try_wait(uint32_t bar, uint32_t parity) {
    uint32_t ok;
    asm volatile(
        "{\n.reg .pred p;\n"
        "mbarrier.try_wait.parity.shared::cta.b64 p, [%1], %2;\n"
        "selp.u32 %0, 1, 0, p;\n}\n"
        : "=r"(ok) : "r"(bar), "r"(parity) : "memory");
    return ok != 0;
}
__device__ __forceinline__ void mbar_wait(uint32_t bar, uint32_t parity) {
    uint32_t it = 0;
    while (!mbar_try_wait(bar, parity)) {
        if (++it > (1u << 24)) __trap();
    }
}
__device__ __forceinline__ void fence_proxy_async() { asm volatile("fence.proxy.async.shared::cta;" ::: "memory"); }
__device__ __forceinline__ void wgmma_fence() { asm volatile("wgmma.fence.sync.aligned;" ::: "memory"); }
__device__ __forceinline__ void wgmma_commit() { asm volatile("wgmma.commit_group.sync.aligned;" ::: "memory"); }
template <int N> __device__ __forceinline__ void wgmma_wait() { asm volatile("wgmma.wait_group.sync.aligned %0;" ::"n"(N) : "memory"); }

__device__ __forceinline__ void tma_load_2d(uint32_t dst, const CUtensorMap* map, uint32_t bar, int c0, int c1) {
    asm volatile(
        "cp.async.bulk.tensor.2d.shared::cluster.global.mbarrier::complete_tx::bytes [%0], [%1, {%3, %4}], [%2];"
        ::"r"(dst), "l"(map), "r"(bar), "r"(c0), "r"(c1) : "memory");
}

__device__ __forceinline__ uint64_t make_desc(uint32_t addr, uint32_t lbo_bytes, uint32_t sbo_bytes, uint32_t swz) {
    uint64_t d = 0;
    d |= (uint64_t)((addr & 0x3FFFF) >> 4);
    d |= (uint64_t)((lbo_bytes & 0x3FFFF) >> 4) << 16;
    d |= (uint64_t)((sbo_bytes & 0x3FFFF) >> 4) << 32;
    d |= (uint64_t)swz << 62;
    return d;
}

__device__ __forceinline__ float bf16r(float x) { return __bfloat162float(__float2bfloat16_rn(x)); }
__device__ __forceinline__ uint32_t pack_bf16(float lo, float hi) {
    bf162 v = __floats2bfloat162_rn(lo, hi);
    return *reinterpret_cast<uint32_t*>(&v);
}
__device__ __forceinline__ float bf_lo(uint32_t u) { return __uint_as_float(u << 16); }
__device__ __forceinline__ float bf_hi(uint32_t u) { return __uint_as_float(u & 0xffff0000u); }

__device__ __forceinline__ void wgmma_rs_n32(float* d, uint32_t a0, uint32_t a1, uint32_t a2, uint32_t a3, uint64_t desc) {
    asm volatile(
        "wgmma.mma_async.sync.aligned.m64n32k16.f32.bf16.bf16 "
        "{%0,%1,%2,%3,%4,%5,%6,%7,%8,%9,%10,%11,%12,%13,%14,%15}, {%16,%17,%18,%19}, %20, 1, 1, 1, 0;\n"
        : "+f"(d[0]), "+f"(d[1]), "+f"(d[2]), "+f"(d[3]), "+f"(d[4]), "+f"(d[5]), "+f"(d[6]), "+f"(d[7]),
          "+f"(d[8]), "+f"(d[9]), "+f"(d[10]), "+f"(d[11]), "+f"(d[12]), "+f"(d[13]), "+f"(d[14]), "+f"(d[15])
        : "r"(a0), "r"(a1), "r"(a2), "r"(a3), "l"(desc));
}
__device__ __forceinline__ void wgmma_rs_n24(float* d, uint32_t a0, uint32_t a1, uint32_t a2, uint32_t a3, uint64_t desc) {
    asm volatile(
        "wgmma.mma_async.sync.aligned.m64n24k16.f32.bf16.bf16 "
        "{%0,%1,%2,%3,%4,%5,%6,%7,%8,%9,%10,%11}, {%12,%13,%14,%15}, %16, 1, 1, 1, 0;\n"
        : "+f"(d[0]), "+f"(d[1]), "+f"(d[2]), "+f"(d[3]), "+f"(d[4]), "+f"(d[5]), "+f"(d[6]), "+f"(d[7]),
          "+f"(d[8]), "+f"(d[9]), "+f"(d[10]), "+f"(d[11])
        : "r"(a0), "r"(a1), "r"(a2), "r"(a3), "l"(desc));
}
__device__ __forceinline__ void wgmma_rs_n16(float* d, uint32_t a0, uint32_t a1, uint32_t a2, uint32_t a3, uint64_t desc) {
    asm volatile(
        "wgmma.mma_async.sync.aligned.m64n16k16.f32.bf16.bf16 "
        "{%0,%1,%2,%3,%4,%5,%6,%7}, {%8,%9,%10,%11}, %12, 1, 1, 1, 0;\n"
        : "+f"(d[0]), "+f"(d[1]), "+f"(d[2]), "+f"(d[3]), "+f"(d[4]), "+f"(d[5]), "+f"(d[6]), "+f"(d[7])
        : "r"(a0), "r"(a1), "r"(a2), "r"(a3), "l"(desc));
}
__device__ __forceinline__ void wgmma_rs_n8(float* d, uint32_t a0, uint32_t a1, uint32_t a2, uint32_t a3, uint64_t desc) {
    asm volatile(
        "wgmma.mma_async.sync.aligned.m64n8k16.f32.bf16.bf16 "
        "{%0,%1,%2,%3}, {%4,%5,%6,%7}, %8, 1, 1, 1, 0;\n"
        : "+f"(d[0]), "+f"(d[1]), "+f"(d[2]), "+f"(d[3])
        : "r"(a0), "r"(a1), "r"(a2), "r"(a3), "l"(desc));
}
__device__ __forceinline__ void wgmma_ss_n128(float* d, uint64_t da, uint64_t db) {
    asm volatile(
        "wgmma.mma_async.sync.aligned.m64n128k16.f32.bf16.bf16 "
        "{%0,%1,%2,%3,%4,%5,%6,%7,%8,%9,%10,%11,%12,%13,%14,%15,"
        "%16,%17,%18,%19,%20,%21,%22,%23,%24,%25,%26,%27,%28,%29,%30,%31,"
        "%32,%33,%34,%35,%36,%37,%38,%39,%40,%41,%42,%43,%44,%45,%46,%47,"
        "%48,%49,%50,%51,%52,%53,%54,%55,%56,%57,%58,%59,%60,%61,%62,%63}, %64, %65, 1, 1, 1, 0, 1;\n"
        : "+f"(d[0]), "+f"(d[1]), "+f"(d[2]), "+f"(d[3]), "+f"(d[4]), "+f"(d[5]), "+f"(d[6]), "+f"(d[7]),
          "+f"(d[8]), "+f"(d[9]), "+f"(d[10]), "+f"(d[11]), "+f"(d[12]), "+f"(d[13]), "+f"(d[14]), "+f"(d[15]),
          "+f"(d[16]), "+f"(d[17]), "+f"(d[18]), "+f"(d[19]), "+f"(d[20]), "+f"(d[21]), "+f"(d[22]), "+f"(d[23]),
          "+f"(d[24]), "+f"(d[25]), "+f"(d[26]), "+f"(d[27]), "+f"(d[28]), "+f"(d[29]), "+f"(d[30]), "+f"(d[31]),
          "+f"(d[32]), "+f"(d[33]), "+f"(d[34]), "+f"(d[35]), "+f"(d[36]), "+f"(d[37]), "+f"(d[38]), "+f"(d[39]),
          "+f"(d[40]), "+f"(d[41]), "+f"(d[42]), "+f"(d[43]), "+f"(d[44]), "+f"(d[45]), "+f"(d[46]), "+f"(d[47]),
          "+f"(d[48]), "+f"(d[49]), "+f"(d[50]), "+f"(d[51]), "+f"(d[52]), "+f"(d[53]), "+f"(d[54]), "+f"(d[55]),
          "+f"(d[56]), "+f"(d[57]), "+f"(d[58]), "+f"(d[59]), "+f"(d[60]), "+f"(d[61]), "+f"(d[62]), "+f"(d[63])
        : "l"(da), "l"(db));
}
__device__ __forceinline__ void wgmma_ss_n64(float* d, uint64_t da, uint64_t db) {
    asm volatile(
        "wgmma.mma_async.sync.aligned.m64n64k16.f32.bf16.bf16 "
        "{%0,%1,%2,%3,%4,%5,%6,%7,%8,%9,%10,%11,%12,%13,%14,%15,"
        "%16,%17,%18,%19,%20,%21,%22,%23,%24,%25,%26,%27,%28,%29,%30,%31}, %32, %33, 1, 1, 1, 0, 1;\n"
        : "+f"(d[0]), "+f"(d[1]), "+f"(d[2]), "+f"(d[3]), "+f"(d[4]), "+f"(d[5]), "+f"(d[6]), "+f"(d[7]),
          "+f"(d[8]), "+f"(d[9]), "+f"(d[10]), "+f"(d[11]), "+f"(d[12]), "+f"(d[13]), "+f"(d[14]), "+f"(d[15]),
          "+f"(d[16]), "+f"(d[17]), "+f"(d[18]), "+f"(d[19]), "+f"(d[20]), "+f"(d[21]), "+f"(d[22]), "+f"(d[23]),
          "+f"(d[24]), "+f"(d[25]), "+f"(d[26]), "+f"(d[27]), "+f"(d[28]), "+f"(d[29]), "+f"(d[30]), "+f"(d[31])
        : "l"(da), "l"(db));
}
__device__ __forceinline__ void wgmma_ss_n32(float* d, uint64_t da, uint64_t db) {
    asm volatile(
        "wgmma.mma_async.sync.aligned.m64n32k16.f32.bf16.bf16 "
        "{%0,%1,%2,%3,%4,%5,%6,%7,%8,%9,%10,%11,%12,%13,%14,%15}, %16, %17, 1, 1, 1, 0, 1;\n"
        : "+f"(d[0]), "+f"(d[1]), "+f"(d[2]), "+f"(d[3]), "+f"(d[4]), "+f"(d[5]), "+f"(d[6]), "+f"(d[7]),
          "+f"(d[8]), "+f"(d[9]), "+f"(d[10]), "+f"(d[11]), "+f"(d[12]), "+f"(d[13]), "+f"(d[14]), "+f"(d[15])
        : "l"(da), "l"(db));
}

constexpr int CV_R = 41;
constexpr int CV_XT_BYTES = 8 * CV_R * 16;
constexpr int CV_WT_WORDS = 2112;
constexpr int CV_WT_BYTES = CV_WT_WORDS * 4;
constexpr int CV_Y_BYTES = 4096;
constexpr int CV_CH_BYTES = CV_XT_BYTES + CV_WT_BYTES + CV_Y_BYTES;
constexpr int CV_SMEM = 4 * CV_CH_BYTES;

template <int NQ>
__device__ __forceinline__ void conv_phase(float* acc, const uint32_t* wp, uint32_t xt_base) {
#pragma unroll 1
    for (int b8 = 0; b8 < 4; b8++) {
        const int j0 = 32 * NQ + 8 * b8;
        uint32_t w[17];
#pragma unroll
        for (int t = 0; t < 17; t++) w[t] = wp[16 * j0 - 56 + 8 * t];
        wgmma_fence();
#pragma unroll
        for (int j = 0; j < 8; j++) {
            const int e2 = 2 * (3 - (j0 + j));
            const int a = e2 >> 3;
            const int b0 = e2 & 7;
            uint32_t addr = xt_base + (uint32_t)((b0 * CV_R + 8 * NQ + a + 8) * 16);
            uint64_t desc = make_desc(addr, CV_R * 16, 128, 0);
            uint32_t a2 = w[2 * j], a0 = w[2 * j + 1], a1 = w[2 * j + 2];
            if (NQ == 0) wgmma_rs_n32(acc, a0, a1, a2, a0, desc);
            else if (NQ == 1) wgmma_rs_n24(acc + 4, a0, a1, a2, a0, desc);
            else if (NQ == 2) wgmma_rs_n16(acc + 8, a0, a1, a2, a0, desc);
            else wgmma_rs_n8(acc + 12, a0, a1, a2, a0, desc);
        }
        wgmma_commit();
        wgmma_wait<0>();
    }
}

__global__ void __launch_bounds__(512, 1)
conv_kernel(const bf16* __restrict__ kin, const bf16* __restrict__ vin, const bf16* __restrict__ shift_k,
            const bf16* __restrict__ ssm_k, const bf16* __restrict__ ssm_D) {
    extern __shared__ __align__(128) uint8_t smem[];
    const int tid = threadIdx.x;
    const int d0 = blockIdx.x * 4;

    if (tid < 256) {
        const int s0 = tid * 8;
        uint2 kr[11], vr[8];
#pragma unroll
        for (int r = 0; r < 11; r++) {
            int row = s0 - 3 + r;
            kr[r] = (row >= 0) ? __ldg(reinterpret_cast<const uint2*>(kin + (size_t)row * D_ + d0)) : make_uint2(0, 0);
        }
#pragma unroll
        for (int r = 0; r < 8; r++) vr[r] = __ldg(reinterpret_cast<const uint2*>(vin + (size_t)(s0 + r) * D_ + d0));
        uint4 sw0 = __ldg(reinterpret_cast<const uint4*>(shift_k + d0 * 4));
        uint4 sw1 = __ldg(reinterpret_cast<const uint4*>(shift_k + d0 * 4 + 8));
        uint32_t w01[4], w23[4];
        w01[0] = __byte_perm(sw0.x, sw0.z, 0x5410); w01[1] = __byte_perm(sw0.x, sw0.z, 0x7632);
        w01[2] = __byte_perm(sw0.y, sw0.w, 0x5410); w01[3] = __byte_perm(sw0.y, sw0.w, 0x7632);
        w23[0] = __byte_perm(sw1.x, sw1.z, 0x5410); w23[1] = __byte_perm(sw1.x, sw1.z, 0x7632);
        w23[2] = __byte_perm(sw1.y, sw1.w, 0x5410); w23[3] = __byte_perm(sw1.y, sw1.w, 0x7632);
        uint32_t kv01[8], kv23[8];
#pragma unroll
        for (int r = 0; r < 8; r++) {
            bf162 a01 = __hmul2_rn(*reinterpret_cast<bf162*>(&kr[r].x), *reinterpret_cast<bf162*>(&w01[3]));
            bf162 a23 = __hmul2_rn(*reinterpret_cast<bf162*>(&kr[r].y), *reinterpret_cast<bf162*>(&w23[3]));
#pragma unroll
            for (int t = 1; t < 4; t++) {
                a01 = __hadd2_rn(a01, __hmul2_rn(*reinterpret_cast<bf162*>(&kr[r + t].x), *reinterpret_cast<bf162*>(&w01[3 - t])));
                a23 = __hadd2_rn(a23, __hmul2_rn(*reinterpret_cast<bf162*>(&kr[r + t].y), *reinterpret_cast<bf162*>(&w23[3 - t])));
            }
            a01 = __hmul2_rn(a01, *reinterpret_cast<bf162*>(&vr[r].x));
            a23 = __hmul2_rn(a23, *reinterpret_cast<bf162*>(&vr[r].y));
            kv01[r] = *reinterpret_cast<uint32_t*>(&a01);
            kv23[r] = *reinterpret_cast<uint32_t*>(&a23);
        }
        const int off = ((tid & 7) * CV_R + (tid >> 3) + 8) * 16;
        uint4 c0, c1, c2, c3;
        c0.x = __byte_perm(kv01[0], kv01[1], 0x5410); c1.x = __byte_perm(kv01[0], kv01[1], 0x7632);
        c0.y = __byte_perm(kv01[2], kv01[3], 0x5410); c1.y = __byte_perm(kv01[2], kv01[3], 0x7632);
        c0.z = __byte_perm(kv01[4], kv01[5], 0x5410); c1.z = __byte_perm(kv01[4], kv01[5], 0x7632);
        c0.w = __byte_perm(kv01[6], kv01[7], 0x5410); c1.w = __byte_perm(kv01[6], kv01[7], 0x7632);
        c2.x = __byte_perm(kv23[0], kv23[1], 0x5410); c3.x = __byte_perm(kv23[0], kv23[1], 0x7632);
        c2.y = __byte_perm(kv23[2], kv23[3], 0x5410); c3.y = __byte_perm(kv23[2], kv23[3], 0x7632);
        c2.z = __byte_perm(kv23[4], kv23[5], 0x5410); c3.z = __byte_perm(kv23[4], kv23[5], 0x7632);
        c2.w = __byte_perm(kv23[6], kv23[7], 0x5410); c3.w = __byte_perm(kv23[6], kv23[7], 0x7632);
        *reinterpret_cast<uint4*>(smem + 0 * CV_CH_BYTES + off) = c0;
        *reinterpret_cast<uint4*>(smem + 1 * CV_CH_BYTES + off) = c1;
        *reinterpret_cast<uint4*>(smem + 2 * CV_CH_BYTES + off) = c2;
        *reinterpret_cast<uint4*>(smem + 3 * CV_CH_BYTES + off) = c3;
    } else {
        const int u = tid - 256;
        *reinterpret_cast<uint4*>(smem + (u >> 6) * CV_CH_BYTES + (((u >> 3) & 7) * CV_R + (u & 7)) * 16) = make_uint4(0, 0, 0, 0);
        reinterpret_cast<uint32_t*>(smem + (u >> 6) * CV_CH_BYTES + CV_XT_BYTES)[u & 63] = 0;
        uint4 kk[4]; uint32_t prev[4];
#pragma unroll
        for (int c = 0; c < 4; c++) {
            const bf16* kp = ssm_k + (size_t)(d0 + c) * S_ + 8 * u;
            kk[c] = __ldg(reinterpret_cast<const uint4*>(kp));
            prev[c] = (u > 0) ? (uint32_t)__ldg(reinterpret_cast<const unsigned short*>(kp - 1)) : 0u;
        }
#pragma unroll
        for (int c = 0; c < 4; c++) {
            uint4 lo, hi;
            lo.x = (kk[c].x & 0xffffu) | (prev[c] << 16);
            lo.y = __byte_perm(kk[c].x, 0, 0x1032);
            lo.z = __byte_perm(kk[c].y, kk[c].x, 0x7610);
            lo.w = __byte_perm(kk[c].y, 0, 0x1032);
            hi.x = __byte_perm(kk[c].z, kk[c].y, 0x7610);
            hi.y = __byte_perm(kk[c].z, 0, 0x1032);
            hi.z = __byte_perm(kk[c].w, kk[c].z, 0x7610);
            hi.w = __byte_perm(kk[c].w, 0, 0x1032);
            uint4* dst = reinterpret_cast<uint4*>(smem + c * CV_CH_BYTES + CV_XT_BYTES + (64 + 8 * u) * 4);
            dst[0] = lo; dst[1] = hi;
        }
    }
    fence_proxy_async();
    __syncthreads();

    const int wg = tid >> 7;
    const int wq = (tid >> 5) & 3, lane = tid & 31, g = lane >> 2, t = lane & 3;
    uint8_t* chs = smem + wg * CV_CH_BYTES;
    {
        float acc[16];
#pragma unroll
        for (int i = 0; i < 16; i++) acc[i] = 0.f;
        const uint32_t* wp = reinterpret_cast<const uint32_t*>(chs + CV_XT_BYTES) + 64 + 16 * wq + g - 2 * t;
        const uint32_t xt_base = smem_u32(chs);
        conv_phase<0>(acc, wp, xt_base);
        conv_phase<1>(acc, wp, xt_base);
        conv_phase<2>(acc, wp, xt_base);
        conv_phase<3>(acc, wp, xt_base);
        bf16* Y = reinterpret_cast<bf16*>(chs + CV_XT_BYTES + CV_WT_BYTES);
#pragma unroll
        for (int i = 0; i < 16; i++) {
            int n = 8 * (i >> 2) + 2 * t + (i & 1);
            int m = 16 * wq + g + 8 * ((i >> 1) & 1);
            Y[64 * n + m] = __float2bfloat16_rn(acc[i]);
        }
    }
    __syncthreads();
    {
        const int s0 = 4 * tid;
        uint2 dd = __ldg(reinterpret_cast<const uint2*>(ssm_D + d0));
        float Dv[4] = {bf_lo(dd.x), bf_hi(dd.x), bf_lo(dd.y), bf_hi(dd.y)};
        float z[4][4];
        const int xoff = (((s0 >> 3) & 7) * CV_R + (s0 >> 6) + 8) * 16 + (tid & 1) * 8;
#pragma unroll
        for (int c = 0; c < 4; c++) {
            uint2 yv = *reinterpret_cast<const uint2*>(smem + c * CV_CH_BYTES + CV_XT_BYTES + CV_WT_BYTES + s0 * 2);
            uint2 kv = *reinterpret_cast<const uint2*>(smem + c * CV_CH_BYTES + xoff);
            z[c][0] = bf_lo(yv.x) + bf16r(bf_lo(kv.x) * Dv[c]);
            z[c][1] = bf_hi(yv.x) + bf16r(bf_hi(kv.x) * Dv[c]);
            z[c][2] = bf_lo(yv.y) + bf16r(bf_lo(kv.y) * Dv[c]);
            z[c][3] = bf_hi(yv.y) + bf16r(bf_hi(kv.y) * Dv[c]);
        }
#pragma unroll
        for (int r = 0; r < 4; r++) {
            uint2 o;
            o.x = pack_bf16(z[0][r], z[1][r]);
            o.y = pack_bf16(z[2][r], z[3][r]);
            *reinterpret_cast<uint2*>(g_z + (size_t)(s0 + r) * D_ + d0) = o;
        }
    }
}

constexpr int G1_NST = 5;
constexpr int G1_A_BYTES = 131072;
constexpr int G1_STAGE = 16384;
constexpr int G1_SMEM = G1_A_BYTES + G1_NST * G1_STAGE + 256 + 1024;

__device__ __forceinline__ float warp_sum(float v) {
#pragma unroll
    for (int o = 16; o > 0; o >>= 1) v += __shfl_xor_sync(0xffffffffu, v, o);
    return v;
}

__device__ __forceinline__ void ln16(const float* x, float* y) {
    float s = 0.f;
#pragma unroll
    for (int i = 0; i < 16; i++) s += x[i];
    s = warp_sum(s);
    const float mean = s * (1.f / 512.f);
    float q = 0.f;
#pragma unroll
    for (int i = 0; i < 16; i++) { float d = x[i] - mean; q += d * d; }
    q = warp_sum(q);
    const float mb = bf16r(mean);
    const float vb = bf16r(q * (1.f / 512.f));
    const float den = bf16r(sqrtf(bf16r(vb + 1e-5f)));
#pragma unroll
    for (int i = 0; i < 16; i++) y[i] = bf16r(__fdiv_rn(bf16r(x[i] - mb), den));
}

__device__ __forceinline__ float sigmoid_f(float x) {
    return __fdividef(1.f, 1.f + __expf(-x));
}

__global__ void __launch_bounds__(384, 1)
gemm1_kernel(const bf16* __restrict__ xin, const __grid_constant__ CUtensorMap map_g, const __grid_constant__ CUtensorMap map_u) {
    extern __shared__ uint8_t smem_raw[];
    uint8_t* smem = reinterpret_cast<uint8_t*>((reinterpret_cast<uintptr_t>(smem_raw) + 1023) & ~(uintptr_t)1023);
    const uint32_t sA = smem_u32(smem);
    const uint32_t sB = sA + G1_A_BYTES;
    const uint32_t sBar = sB + G1_NST * G1_STAGE;
    const int tid = threadIdx.x, warp = tid >> 5, lane = tid & 31;
    const int mt = blockIdx.x >> 3, ns = blockIdx.x & 7;
    const int row0 = mt * 128, f0 = ns * 224;

    if (tid == 0) {
        for (int i = 0; i < G1_NST; i++) { mbar_init(sBar + 8 * i, 1); mbar_init(sBar + 8 * (G1_NST + i), 1); }
        asm volatile("fence.mbarrier_init.release.cluster;" ::: "memory");
    }
    __syncthreads();

    if (warp == 8 && lane == 0) {
        for (int it = 0; it < G1_NST; it++) {
            const int T = it >> 3, kb = it & 7;
            mbar_expect_tx(sBar + 8 * it, G1_STAGE);
            tma_load_2d(sB + it * G1_STAGE, &map_g, sBar + 8 * it, f0 + 64 * T, 64 * kb);
            tma_load_2d(sB + it * G1_STAGE + 8192, &map_u, sBar + 8 * it, f0 + 64 * T, 64 * kb);
        }
    }

    for (int r = warp; r < 128; r += 12) {
        const int row = row0 + r;
        const uint4* xp = reinterpret_cast<const uint4*>(xin + (size_t)row * D_ + lane * 16);
        const uint4* zp = reinterpret_cast<const uint4*>(g_z + (size_t)row * D_ + lane * 16);
        uint4 xa = __ldg(xp), xb = __ldg(xp + 1);
        uint4 za = zp[0], zb = zp[1];
        float x[16], z[16], q[16], h[16], hn[16];
        uint32_t xw[8] = {xa.x, xa.y, xa.z, xa.w, xb.x, xb.y, xb.z, xb.w};
        uint32_t zw[8] = {za.x, za.y, za.z, za.w, zb.x, zb.y, zb.z, zb.w};
#pragma unroll
        for (int i = 0; i < 8; i++) { x[2 * i] = bf_lo(xw[i]); x[2 * i + 1] = bf_hi(xw[i]); z[2 * i] = bf_lo(zw[i]); z[2 * i + 1] = bf_hi(zw[i]); }
        ln16(x, q);
#pragma unroll
        for (int i = 0; i < 16; i++) h[i] = bf16r(x[i] + bf16r(q[i] * z[i]));
        ln16(h, hn);
        uint4 o0, o1;
        o0.x = pack_bf16(hn[0], hn[1]); o0.y = pack_bf16(hn[2], hn[3]); o0.z = pack_bf16(hn[4], hn[5]); o0.w = pack_bf16(hn[6], hn[7]);
        o1.x = pack_bf16(hn[8], hn[9]); o1.y = pack_bf16(hn[10], hn[11]); o1.z = pack_bf16(hn[12], hn[13]); o1.w = pack_bf16(hn[14], hn[15]);
        const int kb = lane >> 2, c0 = (lane & 3) * 2;
        uint8_t* arow = smem + kb * 16384 + r * 128;
        *reinterpret_cast<uint4*>(arow + ((c0 ^ (r & 7)) * 16)) = o0;
        *reinterpret_cast<uint4*>(arow + (((c0 + 1) ^ (r & 7)) * 16)) = o1;
        if (ns == 0) {
            uint4 h0, h1;
            h0.x = pack_bf16(h[0], h[1]); h0.y = pack_bf16(h[2], h[3]); h0.z = pack_bf16(h[4], h[5]); h0.w = pack_bf16(h[6], h[7]);
            h1.x = pack_bf16(h[8], h[9]); h1.y = pack_bf16(h[10], h[11]); h1.z = pack_bf16(h[12], h[13]); h1.w = pack_bf16(h[14], h[15]);
            uint4* hp = reinterpret_cast<uint4*>(g_h + (size_t)row * D_ + lane * 16);
            hp[0] = h0; hp[1] = h1;
        }
    }
    fence_proxy_async();
    __syncthreads();

    if (warp >= 8) {
        if (warp == 8 && lane == 0) {
            for (int it = G1_NST; it < 32; it++) {
                const int st = it % G1_NST, ph = (it / G1_NST) & 1;
                const int T = it >> 3, kb = it & 7;
                mbar_wait(sBar + 8 * (G1_NST + st), ph ^ 1);
                mbar_expect_tx(sBar + 8 * st, G1_STAGE);
                tma_load_2d(sB + st * G1_STAGE, &map_g, sBar + 8 * st, f0 + 64 * T, 64 * kb);
                tma_load_2d(sB + st * G1_STAGE + 8192, &map_u, sBar + 8 * st, f0 + 64 * T, 64 * kb);
            }
        }
    } else {
        const int wg = warp >> 2, wq = warp & 3, g = lane >> 2, t = lane & 3;
        float acc[2][64];
#pragma unroll 1
        for (int T = wg; T < 4; T += 2) {
#pragma unroll
            for (int i = 0; i < 64; i++) { acc[0][i] = 0.f; acc[1][i] = 0.f; }
            const bool full = (T < 3);
#pragma unroll 1
            for (int kb = 0; kb < 8; kb++) {
                const int it = T * 8 + kb;
                const int st = it % G1_NST, ph = (it / G1_NST) & 1;
                mbar_wait(sBar + 8 * st, ph);
                wgmma_fence();
                const uint32_t bst = sB + st * G1_STAGE;
                if (full) {
#pragma unroll
                    for (int kk = 0; kk < 4; kk++) {
                        uint64_t db = make_desc(bst + kk * 2048, 8192, 1024, 1);
#pragma unroll
                        for (int mh = 0; mh < 2; mh++) {
                            uint64_t da = make_desc(sA + kb * 16384 + mh * 8192 + kk * 32, 16, 1024, 1);
                            wgmma_ss_n128(acc[mh], da, db);
                        }
                    }
                } else {
#pragma unroll
                    for (int kk = 0; kk < 4; kk++) {
                        uint64_t dbg = make_desc(bst + kk * 2048, 8192, 1024, 1);
                        uint64_t dbu = make_desc(bst + 8192 + kk * 2048, 8192, 1024, 1);
#pragma unroll
                        for (int mh = 0; mh < 2; mh++) {
                            uint64_t da = make_desc(sA + kb * 16384 + mh * 8192 + kk * 32, 16, 1024, 1);
                            wgmma_ss_n32(acc[mh], da, dbg);
                            wgmma_ss_n32(acc[mh] + 32, da, dbu);
                        }
                    }
                }
                wgmma_commit();
                wgmma_wait<0>();
                if ((tid & 127) == 0) mbar_arrive(sBar + 8 * (G1_NST + st));
            }
            const int nj = full ? 8 : 4;
#pragma unroll
            for (int mh = 0; mh < 2; mh++) {
#pragma unroll
                for (int j = 0; j < 8; j++) {
                    if (j < nj) {
#pragma unroll
                        for (int hf = 0; hf < 2; hf++) {
                            const int row = row0 + 64 * mh + 16 * wq + g + 8 * hf;
                            const int col = f0 + 64 * T + 8 * j + 2 * t;
                            float g0 = bf16r(acc[mh][4 * j + 2 * hf]), g1 = bf16r(acc[mh][4 * j + 2 * hf + 1]);
                            float u0 = bf16r(acc[mh][32 + 4 * j + 2 * hf]), u1 = bf16r(acc[mh][32 + 4 * j + 2 * hf + 1]);
                            float o0 = bf16r(sigmoid_f(g0)) * u0, o1 = bf16r(sigmoid_f(g1)) * u1;
                            *reinterpret_cast<uint32_t*>(g_hh + (size_t)row * F_ + col) = pack_bf16(o0, o1);
                        }
                    }
                }
            }
        }
    }
}

constexpr int G2_NST = 8;
constexpr int G2_STAGE = 16384 + 8192;
constexpr int G2_SMEM = G2_NST * G2_STAGE + 256 + 1024;
constexpr int G2_KB = F_ / 64;

__global__ void __launch_bounds__(384, 1)
gemm2_kernel(bf16* __restrict__ out, const __grid_constant__ CUtensorMap map_a, const __grid_constant__ CUtensorMap map_b) {
    extern __shared__ uint8_t smem_raw[];
    uint8_t* smem = reinterpret_cast<uint8_t*>((reinterpret_cast<uintptr_t>(smem_raw) + 1023) & ~(uintptr_t)1023);
    const uint32_t sS = smem_u32(smem);
    const uint32_t sBar = sS + G2_NST * G2_STAGE;
    const int tid = threadIdx.x, warp = tid >> 5, lane = tid & 31;
    const int mt = blockIdx.x >> 3, ns = blockIdx.x & 7;
    const int row0 = mt * 128, c0 = ns * 64;

    if (tid == 0) {
        for (int i = 0; i < G2_NST; i++) { mbar_init(sBar + 8 * i, 1); mbar_init(sBar + 8 * (G2_NST + i), 2); }
        asm volatile("fence.mbarrier_init.release.cluster;" ::: "memory");
    }
    __syncthreads();

    if (warp >= 8) {
        if (warp == 8 && lane == 0) {
            for (int it = 0; it < G2_KB; it++) {
                const int st = it % G2_NST, ph = (it / G2_NST) & 1;
                if (it >= G2_NST) mbar_wait(sBar + 8 * (G2_NST + st), ph ^ 1);
                mbar_expect_tx(sBar + 8 * st, G2_STAGE);
                tma_load_2d(sS + st * G2_STAGE, &map_a, sBar + 8 * st, 64 * it, row0);
                tma_load_2d(sS + st * G2_STAGE + 16384, &map_b, sBar + 8 * st, c0, 64 * it);
            }
        }
    } else {
        const int wg = warp >> 2, wq = warp & 3, g = lane >> 2, t = lane & 3;
        float acc[32];
#pragma unroll
        for (int i = 0; i < 32; i++) acc[i] = 0.f;
#pragma unroll 1
        for (int it = 0; it < G2_KB; it++) {
            const int st = it % G2_NST, ph = (it / G2_NST) & 1;
            mbar_wait(sBar + 8 * st, ph);
            wgmma_fence();
            const uint32_t ast = sS + st * G2_STAGE + wg * 8192;
            const uint32_t bst = sS + st * G2_STAGE + 16384;
#pragma unroll
            for (int kk = 0; kk < 4; kk++) {
                uint64_t da = make_desc(ast + kk * 32, 16, 1024, 1);
                uint64_t db = make_desc(bst + kk * 2048, 8192, 1024, 1);
                wgmma_ss_n64(acc, da, db);
            }
            wgmma_commit();
            if (it > 0) {
                wgmma_wait<1>();
                if ((tid & 127) == 0) mbar_arrive(sBar + 8 * (G2_NST + (it - 1) % G2_NST));
            }
        }
        wgmma_wait<0>();
#pragma unroll
        for (int j = 0; j < 8; j++) {
#pragma unroll
            for (int hf = 0; hf < 2; hf++) {
                const int row = row0 + 64 * wg + 16 * wq + g + 8 * hf;
                const int col = c0 + 8 * j + 2 * t;
                uint32_t hv = *reinterpret_cast<const uint32_t*>(g_h + (size_t)row * D_ + col);
                float o0 = bf_lo(hv) + bf16r(acc[4 * j + 2 * hf]);
                float o1 = bf_hi(hv) + bf16r(acc[4 * j + 2 * hf + 1]);
                *reinterpret_cast<uint32_t*>(out + (size_t)row * D_ + col) = pack_bf16(o0, o1);
            }
        }
    }
}

typedef CUresult (*PFN_encodeTiled)(CUtensorMap*, CUtensorMapDataType, cuuint32_t, void*, const cuuint64_t*, const cuuint64_t*,
                                    const cuuint32_t*, const cuuint32_t*, CUtensorMapInterleave, CUtensorMapSwizzle,
                                    CUtensorMapL2promotion, CUtensorMapFloatOOBfill);

static void make_map(PFN_encodeTiled enc, CUtensorMap* m, const void* ptr, uint64_t inner, uint64_t outer, uint32_t box_inner, uint32_t box_outer) {
    cuuint64_t dims[2] = {inner, outer};
    cuuint64_t strides[1] = {inner * 2};
    cuuint32_t box[2] = {box_inner, box_outer};
    cuuint32_t es[2] = {1, 1};
    enc(m, CU_TENSOR_MAP_DATA_TYPE_BFLOAT16, 2, const_cast<void*>(ptr), dims, strides, box, es, CU_TENSOR_MAP_INTERLEAVE_NONE,
        CU_TENSOR_MAP_SWIZZLE_128B, CU_TENSOR_MAP_L2_PROMOTION_L2_256B, CU_TENSOR_MAP_FLOAT_OOB_FILL_NONE);
}

extern "C" void kernel_launch(void* const* d_in, const int* in_sizes, int n_in, void* d_out, int out_size) {
    const bf16* A_q = (const bf16*)d_in[0];
    const bf16* A_k = (const bf16*)d_in[1];
    const bf16* A_v = (const bf16*)d_in[2];
    const bf16* A_shift = (const bf16*)d_in[3];
    const bf16* A_ssmk = (const bf16*)d_in[4];
    const bf16* A_ssmD = (const bf16*)d_in[5];
    const bf16* w_gate = (const bf16*)d_in[7];
    const bf16* w_up = (const bf16*)d_in[8];
    const bf16* w_down = (const bf16*)d_in[9];

    static bool init = false;
    static CUtensorMap map_g, map_u, map_hh, map_d;
    static const void* cached[3] = {nullptr, nullptr, nullptr};
    if (!init || cached[0] != w_gate || cached[1] != w_up || cached[2] != w_down) {
        void* fn = nullptr;
        cudaDriverEntryPointQueryResult qres;
        cudaGetDriverEntryPoint("cuTensorMapEncodeTiled", &fn, cudaEnableDefault, &qres);
        PFN_encodeTiled enc = (PFN_encodeTiled)fn;
        void* hh_ptr = nullptr;
        cudaGetSymbolAddress(&hh_ptr, g_hh);
        make_map(enc, &map_g, w_gate, F_, D_, 64, 64);
        make_map(enc, &map_u, w_up, F_, D_, 64, 64);
        make_map(enc, &map_hh, hh_ptr, F_, S_, 64, 128);
        make_map(enc, &map_d, w_down, D_, F_, 64, 64);
        cudaFuncSetAttribute(conv_kernel, cudaFuncAttributeMaxDynamicSharedMemorySize, CV_SMEM);
        cudaFuncSetAttribute(gemm1_kernel, cudaFuncAttributeMaxDynamicSharedMemorySize, G1_SMEM);
        cudaFuncSetAttribute(gemm2_kernel, cudaFuncAttributeMaxDynamicSharedMemorySize, G2_SMEM);
        cached[0] = w_gate; cached[1] = w_up; cached[2] = w_down;
        init = true;
    }
    conv_kernel<<<128, 512, CV_SMEM>>>(A_k, A_v, A_shift, A_ssmk, A_ssmD);
    gemm1_kernel<<<128, 384, G1_SMEM>>>(A_q, map_g, map_u);
    gemm2_kernel<<<128, 384, G2_SMEM>>>((bf16*)d_out, map_hh, map_d);
}
```

```cpp
#include <cuda_runtime.h>
#include <cuda_bf16.h>
#include <cuda.h>
#include <stdint.h>

typedef __nv_bfloat16 bf16;
typedef __nv_bfloat162 bf162;

constexpr int S_ = 2048, D_ = 512, F_ = 1792;

__device__ __align__(1024) bf16 g_hb[S_ * D_];
__device__ __align__(1024) bf16 g_hh[S_ * F_];
__device__ __align__(128) uint32_t g_stats[S_];
__device__ unsigned int g_bar;
__device__ unsigned int g_c1;
__device__ __align__(16) unsigned int g_c2[128];
__device__ unsigned int g_c3;

#define TS_INIT()
#define TS_DUMP()
#define TS(k, i, cond)

__device__ __forceinline__ uint32_t smem_u32(const void* p) { return (uint32_t)__cvta_generic_to_shared(p); }

__device__ __forceinline__ void mbar_init(uint32_t bar, uint32_t count) {
    asm volatile("mbarrier.init.shared::cta.b64 [%0], %1;" ::"r"(bar), "r"(count) : "memory");
}
__device__ __forceinline__ void mbar_expect_tx(uint32_t bar, uint32_t bytes) {
    asm volatile("mbarrier.arrive.expect_tx.shared::cta.b64 _, [%0], %1;" ::"r"(bar), "r"(bytes) : "memory");
}
__device__ __forceinline__ void mbar_arrive(uint32_t bar) {
    asm volatile("mbarrier.arrive.shared::cta.b64 _, [%0];" ::"r"(bar) : "memory");
}
__device__ __forceinline__ uint32_t mapa(uint32_t addr, uint32_t rank) {
    uint32_t r;
    asm volatile("mapa.shared::cluster.u32 %0, %1, %2;" : "=r"(r) : "r"(addr), "r"(rank));
    return r;
}
__device__ __forceinline__ void mbar_arrive_cluster(uint32_t cluster_addr) {
    asm volatile("mbarrier.arrive.shared::cluster.b64 _, [%0];" ::"r"(cluster_addr) : "memory");
}
__device__ __forceinline__ void mbar_wait(uint32_t bar, uint32_t parity) {
    asm volatile(
        "{\n.reg .pred p;\n.reg .u32 c;\n"
        "mov.u32 c, 0;\n"
        "WAIT_%=:\n"
        "mbarrier.try_wait.parity.shared::cta.b64 p, [%0], %1;\n"
        "@p bra DONE_%=;\n"
        "add.u32 c, c, 1;\n"
        "setp.lt.u32 p, c, 4194304;\n"
        "@p bra WAIT_%=;\n"
        "DONE_%=:\n}\n"
        ::"r"(bar), "r"(parity) : "memory");
}
__device__ __forceinline__ void wait_counter(const unsigned int* p, unsigned int target) {
    unsigned int v, it = 0;
    do {
        asm volatile("ld.acquire.gpu.global.u32 %0, [%1];" : "=r"(v) : "l"(p) : "memory");
        if (++it > (1u << 24)) break;
    } while (v < target);
}
__device__ __forceinline__ void cluster_arrive() { asm volatile("barrier.cluster.arrive.release.aligned;" ::: "memory"); }
__device__ __forceinline__ void cluster_wait() { asm volatile("barrier.cluster.wait.acquire.aligned;" ::: "memory"); }
__device__ __forceinline__ void fence_proxy_async() { asm volatile("fence.proxy.async.shared::cta;" ::: "memory"); }
__device__ __forceinline__ void fence_proxy_async_global() { asm volatile("fence.proxy.async.global;" ::: "memory"); }
__device__ __forceinline__ void wgmma_fence() { asm volatile("wgmma.fence.sync.aligned;" ::: "memory"); }
__device__ __forceinline__ void wgmma_commit() { asm volatile("wgmma.commit_group.sync.aligned;" ::: "memory"); }
template <int N> __device__ __forceinline__ void wgmma_wait() { asm volatile("wgmma.wait_group.sync.aligned %0;" ::"n"(N) : "memory"); }

__device__ __forceinline__ void tma_load_2d(uint32_t dst, const CUtensorMap* map, uint32_t bar, int c0, int c1) {
    asm volatile(
        "cp.async.bulk.tensor.2d.shared::cluster.global.mbarrier::complete_tx::bytes [%0], [%1, {%3, %4}], [%2];"
        ::"r"(dst), "l"(map), "r"(bar), "r"(c0), "r"(c1) : "memory");
}
__device__ __forceinline__ void tma_load_2d_mc(uint32_t dst, const CUtensorMap* map, uint32_t bar, int c0, int c1, uint16_t mask) {
    asm volatile(
        "cp.async.bulk.tensor.2d.shared::cluster.global.mbarrier::complete_tx::bytes.multicast::cluster [%0], [%1, {%3, %4}], [%2], %5;"
        ::"r"(dst), "l"(map), "r"(bar), "r"(c0), "r"(c1), "h"(mask) : "memory");
}

__device__ __forceinline__ uint64_t make_desc(uint32_t addr, uint32_t lbo_bytes, uint32_t sbo_bytes, uint32_t swz) {
    uint64_t d = 0;
    d |= (uint64_t)((addr & 0x3FFFF) >> 4);
    d |= (uint64_t)((lbo_bytes & 0x3FFFF) >> 4) << 16;
    d |= (uint64_t)((sbo_bytes & 0x3FFFF) >> 4) << 32;
    d |= (uint64_t)swz << 62;
    return d;
}

__device__ __forceinline__ float bf16r(float x) { return __bfloat162float(__float2bfloat16_rn(x)); }
__device__ __forceinline__ uint32_t pack_bf16(float lo, float hi) {
    bf162 v = __floats2bfloat162_rn(lo, hi);
    return *reinterpret_cast<uint32_t*>(&v);
}
__device__ __forceinline__ float bf_lo(uint32_t u) { return __uint_as_float(u << 16); }
__device__ __forceinline__ float bf_hi(uint32_t u) { return __uint_as_float(u & 0xffff0000u); }
__device__ __forceinline__ void bf16r2(float& a, float& b) {
    const uint32_t p = pack_bf16(a, b);
    a = bf_lo(p); b = bf_hi(p);
}

__device__ __forceinline__ void stmatrix_x4(uint32_t addr, uint32_t r0, uint32_t r1, uint32_t r2, uint32_t r3) {
    asm volatile("stmatrix.sync.aligned.m8n8.x4.shared.b16 [%0], {%1,%2,%3,%4};" ::"r"(addr), "r"(r0), "r"(r1), "r"(r2), "r"(r3) : "memory");
}

template <int OFF>
__device__ __forceinline__ void wgmma_rs_n128(float* d, uint32_t a0, uint32_t a1, uint32_t a2, uint32_t a3, uint32_t dlo, uint32_t dhi) {
    asm volatile(
        "{\n.reg .b64 dsc;\n.reg .b32 lo;\nadd.s32 lo, %68, %70;\nmov.b64 dsc, {lo, %69};\n"
        "wgmma.mma_async.sync.aligned.m64n128k16.f32.bf16.bf16 "
        "{%0,%1,%2,%3,%4,%5,%6,%7,%8,%9,%10,%11,%12,%13,%14,%15,%16,%17,%18,%19,%20,%21,%22,%23,%24,%25,%26,%27,%28,%29,%30,%31,%32,%33,%34,%35,%36,%37,%38,%39,%40,%41,%42,%43,%44,%45,%46,%47,%48,%49,%50,%51,%52,%53,%54,%55,%56,%57,%58,%59,%60,%61,%62,%63}, {%64,%65,%66,%67}, dsc, 1, 1, 1, 0;\n}\n"
        : "+f"(d[0]), "+f"(d[1]), "+f"(d[2]), "+f"(d[3]), "+f"(d[4]), "+f"(d[5]), "+f"(d[6]), "+f"(d[7]), "+f"(d[8]), "+f"(d[9]), "+f"(d[10]), "+f"(d[11]), "+f"(d[12]), "+f"(d[13]), "+f"(d[14]), "+f"(d[15]), "+f"(d[16]), "+f"(d[17]), "+f"(d[18]), "+f"(d[19]), "+f"(d[20]), "+f"(d[21]), "+f"(d[22]), "+f"(d[23]), "+f"(d[24]), "+f"(d[25]), "+f"(d[26]), "+f"(d[27]), "+f"(d[28]), "+f"(d[29]), "+f"(d[30]), "+f"(d[31]), "+f"(d[32]), "+f"(d[33]), "+f"(d[34]), "+f"(d[35]), "+f"(d[36]), "+f"(d[37]), "+f"(d[38]), "+f"(d[39]), "+f"(d[40]), "+f"(d[41]), "+f"(d[42]), "+f"(d[43]), "+f"(d[44]), "+f"(d[45]), "+f"(d[46]), "+f"(d[47]), "+f"(d[48]), "+f"(d[49]), "+f"(d[50]), "+f"(d[51]), "+f"(d[52]), "+f"(d[53]), "+f"(d[54]), "+f"(d[55]), "+f"(d[56]), "+f"(d[57]), "+f"(d[58]), "+f"(d[59]), "+f"(d[60]), "+f"(d[61]), "+f"(d[62]), "+f"(d[63])
        : "r"(a0), "r"(a1), "r"(a2), "r"(a3), "r"(dlo), "r"(dhi), "n"(OFF));
}
template <int OFF>
__device__ __forceinline__ void wgmma_rs_n96(float* d, uint32_t a0, uint32_t a1, uint32_t a2, uint32_t a3, uint32_t dlo, uint32_t dhi) {
    asm volatile(
        "{\n.reg .b64 dsc;\n.reg .b32 lo;\nadd.s32 lo, %52, %54;\nmov.b64 dsc, {lo, %53};\n"
        "wgmma.mma_async.sync.aligned.m64n96k16.f32.bf16.bf16 "
        "{%0,%1,%2,%3,%4,%5,%6,%7,%8,%9,%10,%11,%12,%13,%14,%15,%16,%17,%18,%19,%20,%21,%22,%23,%24,%25,%26,%27,%28,%29,%30,%31,%32,%33,%34,%35,%36,%37,%38,%39,%40,%41,%42,%43,%44,%45,%46,%47}, {%48,%49,%50,%51}, dsc, 1, 1, 1, 0;\n}\n"
        : "+f"(d[0]), "+f"(d[1]), "+f"(d[2]), "+f"(d[3]), "+f"(d[4]), "+f"(d[5]), "+f"(d[6]), "+f"(d[7]), "+f"(d[8]), "+f"(d[9]), "+f"(d[10]), "+f"(d[11]), "+f"(d[12]), "+f"(d[13]), "+f"(d[14]), "+f"(d[15]), "+f"(d[16]), "+f"(d[17]), "+f"(d[18]), "+f"(d[19]), "+f"(d[20]), "+f"(d[21]), "+f"(d[22]), "+f"(d[23]), "+f"(d[24]), "+f"(d[25]), "+f"(d[26]), "+f"(d[27]), "+f"(d[28]), "+f"(d[29]), "+f"(d[30]), "+f"(d[31]), "+f"(d[32]), "+f"(d[33]), "+f"(d[34]), "+f"(d[35]), "+f"(d[36]), "+f"(d[37]), "+f"(d[38]), "+f"(d[39]), "+f"(d[40]), "+f"(d[41]), "+f"(d[42]), "+f"(d[43]), "+f"(d[44]), "+f"(d[45]), "+f"(d[46]), "+f"(d[47])
        : "r"(a0), "r"(a1), "r"(a2), "r"(a3), "r"(dlo), "r"(dhi), "n"(OFF));
}
template <int OFF>
__device__ __forceinline__ void wgmma_rs_n64(float* d, uint32_t a0, uint32_t a1, uint32_t a2, uint32_t a3, uint32_t dlo, uint32_t dhi) {
    asm volatile(
        "{\n.reg .b64 dsc;\n.reg .b32 lo;\nadd.s32 lo, %36, %38;\nmov.b64 dsc, {lo, %37};\n"
        "wgmma.mma_async.sync.aligned.m64n64k16.f32.bf16.bf16 "
        "{%0,%1,%2,%3,%4,%5,%6,%7,%8,%9,%10,%11,%12,%13,%14,%15,%16,%17,%18,%19,%20,%21,%22,%23,%24,%25,%26,%27,%28,%29,%30,%31}, {%32,%33,%34,%35}, dsc, 1, 1, 1, 0;\n}\n"
        : "+f"(d[0]), "+f"(d[1]), "+f"(d[2]), "+f"(d[3]), "+f"(d[4]), "+f"(d[5]), "+f"(d[6]), "+f"(d[7]), "+f"(d[8]), "+f"(d[9]), "+f"(d[10]), "+f"(d[11]), "+f"(d[12]), "+f"(d[13]), "+f"(d[14]), "+f"(d[15]), "+f"(d[16]), "+f"(d[17]), "+f"(d[18]), "+f"(d[19]), "+f"(d[20]), "+f"(d[21]), "+f"(d[22]), "+f"(d[23]), "+f"(d[24]), "+f"(d[25]), "+f"(d[26]), "+f"(d[27]), "+f"(d[28]), "+f"(d[29]), "+f"(d[30]), "+f"(d[31])
        : "r"(a0), "r"(a1), "r"(a2), "r"(a3), "r"(dlo), "r"(dhi), "n"(OFF));
}
template <int OFF>
__device__ __forceinline__ void wgmma_rs_n32(float* d, uint32_t a0, uint32_t a1, uint32_t a2, uint32_t a3, uint32_t dlo, uint32_t dhi) {
    asm volatile(
        "{\n.reg .b64 dsc;\n.reg .b32 lo;\nadd.s32 lo, %20, %22;\nmov.b64 dsc, {lo, %21};\n"
        "wgmma.mma_async.sync.aligned.m64n32k16.f32.bf16.bf16 "
        "{%0,%1,%2,%3,%4,%5,%6,%7,%8,%9,%10,%11,%12,%13,%14,%15}, {%16,%17,%18,%19}, dsc, 1, 1, 1, 0;\n}\n"
        : "+f"(d[0]), "+f"(d[1]), "+f"(d[2]), "+f"(d[3]), "+f"(d[4]), "+f"(d[5]), "+f"(d[6]), "+f"(d[7]), "+f"(d[8]), "+f"(d[9]), "+f"(d[10]), "+f"(d[11]), "+f"(d[12]), "+f"(d[13]), "+f"(d[14]), "+f"(d[15])
        : "r"(a0), "r"(a1), "r"(a2), "r"(a3), "r"(dlo), "r"(dhi), "n"(OFF));
}
template <int OFF>
__device__ __forceinline__ void wgmma_rs_n8(float* d, uint32_t a0, uint32_t a1, uint32_t a2, uint32_t a3, uint32_t dlo, uint32_t dhi) {
    asm volatile(
        "{\n.reg .b64 dsc;\n.reg .b32 lo;\nadd.s32 lo, %8, %10;\nmov.b64 dsc, {lo, %9};\n"
        "wgmma.mma_async.sync.aligned.m64n8k16.f32.bf16.bf16 "
        "{%0,%1,%2,%3}, {%4,%5,%6,%7}, dsc, 1, 1, 1, 0;\n}\n"
        : "+f"(d[0]), "+f"(d[1]), "+f"(d[2]), "+f"(d[3])
        : "r"(a0), "r"(a1), "r"(a2), "r"(a3), "r"(dlo), "r"(dhi), "n"(OFF));
}
template <int OFF>
__device__ __forceinline__ void wgmma_rst_n128(float* d, const uint32_t* a, uint32_t dlo, uint32_t dhi) {
    asm volatile(
        "{\n.reg .b64 dsc;\n.reg .b32 lo;\nadd.s32 lo, %68, %70;\nmov.b64 dsc, {lo, %69};\n"
        "wgmma.mma_async.sync.aligned.m64n128k16.f32.bf16.bf16 "
        "{%0,%1,%2,%3,%4,%5,%6,%7,%8,%9,%10,%11,%12,%13,%14,%15,%16,%17,%18,%19,%20,%21,%22,%23,%24,%25,%26,%27,%28,%29,%30,%31,%32,%33,%34,%35,%36,%37,%38,%39,%40,%41,%42,%43,%44,%45,%46,%47,%48,%49,%50,%51,%52,%53,%54,%55,%56,%57,%58,%59,%60,%61,%62,%63}, {%64,%65,%66,%67}, dsc, 1, 1, 1, 1;\n}\n"
        : "+f"(d[0]), "+f"(d[1]), "+f"(d[2]), "+f"(d[3]), "+f"(d[4]), "+f"(d[5]), "+f"(d[6]), "+f"(d[7]), "+f"(d[8]), "+f"(d[9]), "+f"(d[10]), "+f"(d[11]), "+f"(d[12]), "+f"(d[13]), "+f"(d[14]), "+f"(d[15]), "+f"(d[16]), "+f"(d[17]), "+f"(d[18]), "+f"(d[19]), "+f"(d[20]), "+f"(d[21]), "+f"(d[22]), "+f"(d[23]), "+f"(d[24]), "+f"(d[25]), "+f"(d[26]), "+f"(d[27]), "+f"(d[28]), "+f"(d[29]), "+f"(d[30]), "+f"(d[31]), "+f"(d[32]), "+f"(d[33]), "+f"(d[34]), "+f"(d[35]), "+f"(d[36]), "+f"(d[37]), "+f"(d[38]), "+f"(d[39]), "+f"(d[40]), "+f"(d[41]), "+f"(d[42]), "+f"(d[43]), "+f"(d[44]), "+f"(d[45]), "+f"(d[46]), "+f"(d[47]), "+f"(d[48]), "+f"(d[49]), "+f"(d[50]), "+f"(d[51]), "+f"(d[52]), "+f"(d[53]), "+f"(d[54]), "+f"(d[55]), "+f"(d[56]), "+f"(d[57]), "+f"(d[58]), "+f"(d[59]), "+f"(d[60]), "+f"(d[61]), "+f"(d[62]), "+f"(d[63])
        : "r"(a[0]), "r"(a[1]), "r"(a[2]), "r"(a[3]), "r"(dlo), "r"(dhi), "n"(OFF));
}
template <int OFF>
__device__ __forceinline__ void wgmma_rst_n64(float* d, const uint32_t* a, uint32_t dlo, uint32_t dhi) {
    asm volatile(
        "{\n.reg .b64 dsc;\n.reg .b32 lo;\nadd.s32 lo, %36, %38;\nmov.b64 dsc, {lo, %37};\n"
        "wgmma.mma_async.sync.aligned.m64n64k16.f32.bf16.bf16 "
        "{%0,%1,%2,%3,%4,%5,%6,%7,%8,%9,%10,%11,%12,%13,%14,%15,%16,%17,%18,%19,%20,%21,%22,%23,%24,%25,%26,%27,%28,%29,%30,%31}, {%32,%33,%34,%35}, dsc, 1, 1, 1, 1;\n}\n"
        : "+f"(d[0]), "+f"(d[1]), "+f"(d[2]), "+f"(d[3]), "+f"(d[4]), "+f"(d[5]), "+f"(d[6]), "+f"(d[7]), "+f"(d[8]), "+f"(d[9]), "+f"(d[10]), "+f"(d[11]), "+f"(d[12]), "+f"(d[13]), "+f"(d[14]), "+f"(d[15]), "+f"(d[16]), "+f"(d[17]), "+f"(d[18]), "+f"(d[19]), "+f"(d[20]), "+f"(d[21]), "+f"(d[22]), "+f"(d[23]), "+f"(d[24]), "+f"(d[25]), "+f"(d[26]), "+f"(d[27]), "+f"(d[28]), "+f"(d[29]), "+f"(d[30]), "+f"(d[31])
        : "r"(a[0]), "r"(a[1]), "r"(a[2]), "r"(a[3]), "r"(dlo), "r"(dhi), "n"(OFF));
}

constexpr int NSLOT = 14;
constexpr int SLOT = 16384;
constexpr int X_OFF = 10 * SLOT;
constexpr int BAR_OFF = NSLOT * SLOT;
constexpr int ONES_OFF = BAR_OFF + 512;
constexpr int SMEM_BYTES = BAR_OFF + 800 + 1024;
constexpr int PRE = 3;
constexpr int G1_LAG = 4;
constexpr int A_SLOT0 = 6;
constexpr int CV_BASE = PRE * SLOT;
constexpr int CV_R = 156;
constexpr int CV_XT_BYTES = 2 * CV_R * 16;
constexpr int CV_WT_BYTES = 2064 * 4;
constexpr int CV_P_BYTES = 3072 * 4;
constexpr int CV_CH_BYTES = CV_XT_BYTES + CV_WT_BYTES + 2 * CV_P_BYTES + 80;
static_assert(CV_CH_BYTES % 128 == 16, "channel pitch");
constexpr int CV_XS_OFF = CV_BASE + 4 * CV_CH_BYTES;
constexpr int CV_XS_PITCH = 4096 + 16;
constexpr int CV_ST_OFF = CV_XS_OFF + 4 * CV_XS_PITCH;
static_assert(CV_XS_OFF % 16 == 0 && CV_ST_OFF % 16 == 0 && CV_ST_OFF + 8192 <= BAR_OFF, "conv layout");
constexpr int cv_stage(int c) { return (CV_BASE + c * CV_CH_BYTES + CV_XT_BYTES + CV_WT_BYTES + 1023) / 1024 * 1024; }
constexpr int CV_KS_OFF = cv_stage(0), CV_VS_OFF = cv_stage(1), CV_XI_OFF = cv_stage(2);
static_assert(CV_KS_OFF + 1024 + 16384 <= CV_BASE + CV_CH_BYTES && CV_VS_OFF + 16384 <= CV_BASE + 2 * CV_CH_BYTES && CV_XI_OFF + 16384 <= CV_BASE + 3 * CV_CH_BYTES, "staging");

__device__ __forceinline__ void conv_load(uint32_t (&w)[6], const uint32_t* wp) {
#pragma unroll
    for (int s = 0; s < 2; s++) { w[3 * s] = wp[64 * s - 8]; w[3 * s + 1] = wp[64 * s]; w[3 * s + 2] = wp[64 * s + 8]; }
}
template <int L, int OFF>
__device__ __forceinline__ void conv_mma1(float* acc, uint32_t a2, uint32_t a0, uint32_t a1, uint32_t dlo, uint32_t dhi) {
    if (L == 0) wgmma_rs_n128<OFF>(acc, a0, a1, a2, a0, dlo, dhi);
    else if (L == 1) wgmma_rs_n128<OFF>(acc, a0, a1, a2, a0, dlo, dhi);
    else if (L == 2) wgmma_rs_n96<OFF>(acc, a0, a1, a2, a0, dlo, dhi);
    else if (L == 3) wgmma_rs_n96<OFF>(acc, a0, a1, a2, a0, dlo, dhi);
    else if (L == 4) wgmma_rs_n64<OFF>(acc, a0, a1, a2, a0, dlo, dhi);
    else if (L == 5) wgmma_rs_n64<OFF>(acc, a0, a1, a2, a0, dlo, dhi);
    else if (L == 6) wgmma_rs_n32<OFF>(acc, a0, a1, a2, a0, dlo, dhi);
    else wgmma_rs_n32<OFF>(acc, a0, a1, a2, a0, dlo, dhi);
}
template <int B>
__device__ __forceinline__ void conv_issue(float* acc, const uint32_t (&w)[6], uint32_t dlo, uint32_t dhi) {
    wgmma_fence();
    conv_mma1<(B >> 1), 8 * B + 0>(acc, w[0], w[1], w[2], dlo, dhi);
    conv_mma1<(B >> 1), 8 * B + 4>(acc, w[3], w[4], w[5], dlo, dhi);
    wgmma_commit();
}
template <int B>
__device__ __forceinline__ void conv_pair(float* acc, uint32_t (&q0)[6], uint32_t (&q1)[6], const uint32_t* wp, uint32_t dlo, uint32_t dhi) {
    if (B > 0 && (B & 3) == 0) wgmma_wait<0>();
    conv_issue<B>(acc, q0, dlo, dhi);
    if ((B & 3) != 0) wgmma_wait<1>();
    conv_load(q1, wp + 128 * (B + 1));
    conv_issue<B + 1>(acc, q1, dlo, dhi);
    if (B + 2 < 16) {
        wgmma_wait<1>();
        conv_load(q0, wp + 128 * (B + 2));
    }
}
__device__ __forceinline__ void conv_mma(float* acc, const uint32_t* wp, uint32_t xt_base) {
    uint32_t q0[6], q1[6];
    const uint64_t desc0 = make_desc(xt_base, CV_R * 16, 128, 0);
    const uint32_t dlo = (uint32_t)desc0, dhi = (uint32_t)(desc0 >> 32);
    conv_load(q0, wp);
    conv_pair<0>(acc, q0, q1, wp, dlo, dhi);
    conv_pair<2>(acc, q0, q1, wp, dlo, dhi);
    conv_pair<4>(acc, q0, q1, wp, dlo, dhi);
    conv_pair<6>(acc, q0, q1, wp, dlo, dhi);
    conv_pair<8>(acc, q0, q1, wp, dlo, dhi);
    conv_pair<10>(acc, q0, q1, wp, dlo, dhi);
    conv_pair<12>(acc, q0, q1, wp, dlo, dhi);
    conv_pair<14>(acc, q0, q1, wp, dlo, dhi);
    wgmma_wait<0>();
}
__device__ __forceinline__ float warp_sum(float v) {
#pragma unroll
    for (int o = 16; o > 0; o >>= 1) v += __shfl_xor_sync(0xffffffffu, v, o);
    return v;
}
__device__ __forceinline__ float sigmoid_f(float x) {
    float e, r;
    asm("ex2.approx.ftz.f32 %0, %1;" : "=f"(e) : "f"(x * -1.4426950408889634f));
    asm("rcp.approx.ftz.f32 %0, %1;" : "=f"(r) : "f"(1.f + e));
    return r;
}
__device__ __forceinline__ void st_async_v4(uint32_t addr, const uint32_t (&c)[4], uint32_t bar) {
    asm volatile("st.async.weak.shared::cluster.mbarrier::complete_tx::bytes.v4.b32 [%0], {%1,%2,%3,%4}, [%5];"
                 ::"r"(addr), "r"(c[0]), "r"(c[1]), "r"(c[2]), "r"(c[3]), "r"(bar) : "memory");
}

__device__ __forceinline__ void load_chunk_t(uint32_t addr_rows, int lane, uint32_t (&r)[4]) {
    asm volatile("ldmatrix.sync.aligned.m8n8.x4.trans.shared.b16 {%0,%1,%2,%3}, [%4];"
                 : "=r"(r[0]), "=r"(r[1]), "=r"(r[2]), "=r"(r[3]) : "r"(addr_rows + lane * 16) : "memory");
    const bool b0 = lane & 1, b1 = lane & 2;
    uint32_t x, y;
    x = b0 ? r[0] : r[1]; y = b0 ? r[2] : r[3];
    x = __shfl_xor_sync(0xffffffffu, x, 1); y = __shfl_xor_sync(0xffffffffu, y, 1);
    if (b0) { r[0] = x; r[2] = y; } else { r[1] = x; r[3] = y; }
    x = b1 ? r[0] : r[2]; y = b1 ? r[1] : r[3];
    x = __shfl_xor_sync(0xffffffffu, x, 2); y = __shfl_xor_sync(0xffffffffu, y, 2);
    if (b1) { r[0] = x; r[1] = y; } else { r[2] = x; r[3] = y; }
}

template <bool FULL>
__device__ __forceinline__ void gemm1_pass(int T, const uint32_t (&a)[32][4], float inv0, float inv1, uint32_t sb, uint32_t peer,
                                           int row0, int f0, int tid, int wg) {
    const int warp = tid >> 5, lane = tid & 31;
    const uint32_t barFull = sb + BAR_OFF, barEmpty = barFull + 8 * NSLOT;
    const uint64_t d0_ = FULL ? make_desc(sb, 8192, 1024, 1) : make_desc(sb, 4096, 512, 2);
    const uint32_t dlo0 = (uint32_t)d0_, dhi = (uint32_t)(d0_ >> 32);
    const uint32_t peerEmpty = mapa(barEmpty, peer);
    int st = (T * 8) % NSLOT, ph = ((T * 8) / NSLOT) & 1;
    constexpr int UO = FULL ? 32 : 16;
    float acc[2 * UO];
#pragma unroll
    for (int i = 0; i < 2 * UO; i++) acc[i] = 0.f;
#pragma unroll
    for (int kb = 0; kb < 8; kb++) {
        mbar_wait(barFull + 8 * st, ph);
        wgmma_fence();
        const uint32_t dlo = dlo0 + st * (SLOT / 16);
        if (FULL) {
            wgmma_rst_n128<0>(acc, a[4 * kb], dlo, dhi); wgmma_rst_n128<128>(acc, a[4 * kb + 1], dlo, dhi);
            wgmma_rst_n128<256>(acc, a[4 * kb + 2], dlo, dhi); wgmma_rst_n128<384>(acc, a[4 * kb + 3], dlo, dhi);
        } else {
            wgmma_rst_n64<0>(acc, a[4 * kb], dlo, dhi); wgmma_rst_n64<64>(acc, a[4 * kb + 1], dlo, dhi);
            wgmma_rst_n64<128>(acc, a[4 * kb + 2], dlo, dhi); wgmma_rst_n64<192>(acc, a[4 * kb + 3], dlo, dhi);
        }
        wgmma_commit();
        if (kb == G1_LAG) asm volatile("{\n.reg .pred p;\nsetp.eq.s32 p, %0, 0;\n@p bar.arrive 5, 256;\n}\n" ::"r"(wg + T) : "memory");
        if (kb > 0) {
            wgmma_wait<1>();
            if ((tid & 127) == 0) {
                const int pst = (st == 0) ? NSLOT - 1 : st - 1;
                mbar_arrive(barEmpty + 8 * pst);
                mbar_arrive_cluster(peerEmpty + 8 * pst);
            }
        }
        if (++st == NSLOT) { st = 0; ph ^= 1; }
    }
    wgmma_wait<0>();
    if ((tid & 127) == 0) {
        const int pst = (st == 0) ? NSLOT - 1 : st - 1;
        mbar_arrive(barEmpty + 8 * pst);
        mbar_arrive_cluster(peerEmpty + 8 * pst);
    }
    TS(1, 3 + 2 * T, tid == 0);
    TS(2, 12 + T, tid == 128);
    constexpr int NJ = FULL ? 8 : 4;
    uint32_t pk[NJ][2];
#pragma unroll
    for (int j = 0; j < NJ; j++) {
#pragma unroll
        for (int hf = 0; hf < 2; hf++) {
            const float inv = hf ? inv1 : inv0;
            const uint32_t gp = pack_bf16(acc[4 * j + 2 * hf] * inv, acc[4 * j + 2 * hf + 1] * inv);
            const uint32_t up = pack_bf16(acc[UO + 4 * j + 2 * hf] * inv, acc[UO + 4 * j + 2 * hf + 1] * inv);
            const uint32_t sp = pack_bf16(sigmoid_f(bf_lo(gp)), sigmoid_f(bf_hi(gp)));
            const bf162 pr = __hmul2_rn(*reinterpret_cast<const bf162*>(&sp), *reinterpret_cast<const bf162*>(&up));
            pk[j][hf] = *reinterpret_cast<const uint32_t*>(&pr);
        }
    }
    const int ns = f0;
    const int blk = 14 * (ns >> 2) + (FULL ? 4 * T + (ns & 3) : 12 + ((ns & 3) >> 1));
    uint4* dst = reinterpret_cast<uint4*>(g_hh) + ((size_t)(row0 >> 7) * 28 + blk) * 1024 + warp * 128 + (FULL ? 0 : (ns & 1) * 64) + lane;
#pragma unroll
    for (int j = 0; j < NJ; j += 2) dst[(j >> 1) * 32] = make_uint4(pk[j][0], pk[j][1], pk[j + 1][0], pk[j + 1][1]);
    asm volatile("bar.arrive %0, 160;" ::"r"(11 + wg) : "memory");
    TS(1, 4 + 2 * T, tid == 0);
}

constexpr int NA = 6;
__device__ __forceinline__ int g2_slotB(int j) { return 4 + (j & 7); }
__device__ __forceinline__ int g2_fillB(int j) { return 2 + (j >> 3); }
__device__ __forceinline__ int g2_slotA(int j) { return (12 + j % NA) % NSLOT; }
__device__ __forceinline__ int g2_fillA(int j) { return (j % NA < 2 ? 2 : 3) + j / NA; }

__global__ void __cluster_dims__(2, 1, 1) __launch_bounds__(512, 1)
mega_kernel(const bf16* __restrict__ xin, const bf16* __restrict__ kin, const bf16* __restrict__ vin, const bf16* __restrict__ shift_k,
            const bf16* __restrict__ ssm_k, const bf16* __restrict__ ssm_D,
            const bf16* __restrict__ w_gate, const bf16* __restrict__ w_up, const bf16* __restrict__ w_down, bf16* __restrict__ out,
            const __grid_constant__ CUtensorMap map_g, const __grid_constant__ CUtensorMap map_u,
            const __grid_constant__ CUtensorMap map_g32, const __grid_constant__ CUtensorMap map_u32,
            const __grid_constant__ CUtensorMap map_d, const __grid_constant__ CUtensorMap map_d32, const __grid_constant__ CUtensorMap map_k, const __grid_constant__ CUtensorMap map_kh,
            const __grid_constant__ CUtensorMap map_v, const __grid_constant__ CUtensorMap map_x) {
    extern __shared__ uint8_t smem_raw[];
    uint8_t* smem = smem_raw + ((1024u - (smem_u32(smem_raw) & 1023u)) & 1023u);
    const uint32_t sb = smem_u32(smem);
    const uint32_t barFull = sb + BAR_OFF, barEmpty = barFull + 8 * NSLOT, barA = barEmpty + 8 * NSLOT;
    const uint32_t barKV = barA + 64, barXS = barKV + 8, barX = barXS + 8, barKin = barX + 8, barXin = barKin + 8, barAE = barXin + 8, barG1 = barAE + 48, barRdy = barG1 + 8, barKi = barRdy + 8;
    const int tid = threadIdx.x, warp = tid >> 5, lane = tid & 31;
    const int bid = blockIdx.x;
    const int rank = bid & 1;
    const int d0 = bid * 4, dp = (bid >> 1) * 8;
    const int ns = (bid >> 1) & 7, mt1 = 2 * (bid >> 4) + rank;
    const int f0 = ns * 224;
    const int mt2 = bid >> 3, nt = (bid >> 1) & 3;
    TS_INIT();
    TS(0, 0, tid == 0);

    if (tid == 0) {
        for (int i = 0; i < NSLOT; i++) { mbar_init(barFull + 8 * i, 1); mbar_init(barEmpty + 8 * i, 4); }
        for (int i = 0; i < 8; i++) mbar_init(barA + 8 * i, 1);
        mbar_init(barKV, 1);
        mbar_init(barXS, 2);
        mbar_init(barX, 1);
        for (int i = 0; i < NA; i++) mbar_init(barAE + 8 * i, 8);
        mbar_init(barRdy, 2);
        mbar_init(barG1, 1);
        for (int i = 0; i < 4; i++) mbar_init(barKi + 8 * i, 1);
        mbar_init(barKin, 1);
        mbar_init(barXin, 1);
        asm volatile("fence.mbarrier_init.release.cluster;" ::: "memory");
        mbar_expect_tx(barKV, 16384);
        mbar_expect_tx(barXS, 16384);
        mbar_expect_tx(barX, 32768);
        for (int i = 0; i < 4; i++) {
            mbar_expect_tx(barKi + 8 * i, i == 0 ? 8192 + 128 : 8192);
            if (i == 0) tma_load_2d(sb + CV_KS_OFF + 896, &map_kh, barKi, dp, 1024 * rank - 8);
            tma_load_2d(sb + CV_KS_OFF + 1024 + i * 4096, &map_k, barKi + 8 * i, dp, 1024 * rank + 256 * i);
            tma_load_2d(sb + CV_VS_OFF + i * 4096, &map_v, barKi + 8 * i, dp, 1024 * rank + 256 * i);
        }
        mbar_expect_tx(barXin, 16384);
        for (int i = 0; i < 4; i++) tma_load_2d(sb + CV_XI_OFF + i * 4096, &map_x, barXin, dp, 1024 * rank + 256 * i);
    }
    __syncwarp();
    asm volatile("barrier.cluster.arrive.relaxed.aligned;" ::: "memory");
    const uint2 dD = __ldg(reinterpret_cast<const uint2*>(ssm_D + d0));

    if (tid < 256) {
        uint32_t w[4][4];
#pragma unroll
        for (int cp = 0; cp < 4; cp++) {
            const uint4 sw = __ldg(reinterpret_cast<const uint4*>(shift_k + (dp + 2 * cp) * 4));
            w[0][cp] = __byte_perm(sw.x, sw.z, 0x5410); w[1][cp] = __byte_perm(sw.x, sw.z, 0x7632);
            w[2][cp] = __byte_perm(sw.y, sw.w, 0x5410); w[3][cp] = __byte_perm(sw.y, sw.w, 0x7632);
        }
        asm volatile("bar.sync 1, 512;" ::: "memory");
        cluster_wait();
        const int g = lane >> 2, t = lane & 3;
        const uint32_t dbase = mapa(sb, g >> 2);
#pragma unroll 1
        for (int i = 0; i < 4; i++) {
            mbar_wait(barKi + 8 * i, 0);
            const int row = tid + 256 * i;
            const uint4* ks = reinterpret_cast<const uint4*>(smem + CV_KS_OFF + 1024) + row;
            uint4* vs = reinterpret_cast<uint4*>(smem + CV_VS_OFF) + row;
            const uint4 k0 = ks[-3], k1 = ks[-2], k2 = ks[-1], k3 = ks[0], vv = vs[0];
            const uint32_t ka[4][4] = {{k0.x, k0.y, k0.z, k0.w}, {k1.x, k1.y, k1.z, k1.w}, {k2.x, k2.y, k2.z, k2.w}, {k3.x, k3.y, k3.z, k3.w}};
            const uint32_t va[4] = {vv.x, vv.y, vv.z, vv.w};
            uint32_t o[4];
#pragma unroll
            for (int cp = 0; cp < 4; cp++) {
                bf162 acc2 = __hmul2_rn(*reinterpret_cast<const bf162*>(&ka[0][cp]), *reinterpret_cast<const bf162*>(&w[3][cp]));
#pragma unroll
                for (int t = 1; t < 4; t++)
                    acc2 = __hadd2_rn(acc2, __hmul2_rn(*reinterpret_cast<const bf162*>(&ka[t][cp]), *reinterpret_cast<const bf162*>(&w[3 - t][cp])));
                acc2 = __hmul2_rn(acc2, *reinterpret_cast<const bf162*>(&va[cp]));
                o[cp] = *reinterpret_cast<uint32_t*>(&acc2);
            }
            vs[0] = make_uint4(o[0], o[1], o[2], o[3]);
            __syncwarp();
            const int row0 = 32 * warp + 256 * i;
            uint32_t c[4];
            load_chunk_t(sb + CV_VS_OFF + row0 * 16, lane, c);
            const int p = 128 * rank + (row0 >> 3) + t;
            st_async_v4(dbase + CV_BASE + (g & 3) * CV_CH_BYTES + ((p & 1) * CV_R + 127 - (p >> 1)) * 16, c, dbase + BAR_OFF + (barKV - barFull));
        }
    } else {
        const int u = tid - 256;
        const int lrow = bid * 16 + 2 * (u >> 5);
        const uint4* xp = reinterpret_cast<const uint4*>(xin + (size_t)lrow * D_ + lane * 16);
        uint4 xa[2], xb[2];
        xa[0] = __ldg(xp); xb[0] = __ldg(xp + 1); xa[1] = __ldg(xp + 64); xb[1] = __ldg(xp + 65);
        uint4 kk[4]; uint32_t prev[4];
#pragma unroll
        for (int c = 0; c < 4; c++) {
            const bf16* kp = ssm_k + (size_t)(d0 + c) * S_ + 8 * u;
            kk[c] = __ldg(reinterpret_cast<const uint4*>(kp));
            prev[c] = (u > 0) ? (uint32_t)__ldg(reinterpret_cast<const unsigned short*>(kp - 1)) : 0u;
        }
        asm volatile("bar.sync 1, 512;" ::: "memory");
#pragma unroll
        for (int r = 0; r < 2; r++) {
            const uint32_t xw[8] = {xa[r].x, xa[r].y, xa[r].z, xa[r].w, xb[r].x, xb[r].y, xb[r].z, xb[r].w};
            float sm_ = 0.f;
#pragma unroll
            for (int i = 0; i < 8; i++) sm_ += bf_lo(xw[i]) + bf_hi(xw[i]);
            sm_ = warp_sum(sm_);
            const float mean = sm_ * (1.f / 512.f);
            float q = 0.f;
#pragma unroll
            for (int i = 0; i < 8; i++) { float d1 = bf_lo(xw[i]) - mean, d2 = bf_hi(xw[i]) - mean; q += d1 * d1 + d2 * d2; }
            q = warp_sum(q);
            if (lane == 0) {
                g_stats[lrow + r] = pack_bf16(mean, sqrtf(bf16r(bf16r(q * (1.f / 512.f)) + 1e-5f)));
            }
        }
        if (lane == 0) {
            __threadfence();
            const unsigned int old = atomicAdd(&g_bar, 1u);
            if (u == 0) *reinterpret_cast<volatile unsigned int*>(smem + ONES_OFF + 256) = (old / 1024u + 1u) * 1024u;
        }
        __syncwarp();
        if (u < 224) *reinterpret_cast<uint4*>(smem + CV_BASE + (u / 56) * CV_CH_BYTES + (((u % 56) / 28) * CV_R + 128 + (u % 28)) * 16) = make_uint4(0, 0, 0, 0);
        if (u < 64) reinterpret_cast<uint32_t*>(smem + CV_BASE + (u >> 4) * CV_CH_BYTES + CV_XT_BYTES)[u & 15] = 0;
        else if (u < 128) reinterpret_cast<uint32_t*>(smem + ONES_OFF)[u - 64] = 0x3F803F80u;
#pragma unroll
        for (int c = 0; c < 4; c++) {
            uint4 lo, hi;
            lo.x = (kk[c].x & 0xffffu) | (prev[c] << 16);
            lo.y = __byte_perm(kk[c].x, 0, 0x1032);
            lo.z = __byte_perm(kk[c].y, kk[c].x, 0x7610);
            lo.w = __byte_perm(kk[c].y, 0, 0x1032);
            hi.x = __byte_perm(kk[c].z, kk[c].y, 0x7610);
            hi.y = __byte_perm(kk[c].z, 0, 0x1032);
            hi.z = __byte_perm(kk[c].w, kk[c].z, 0x7610);
            hi.w = __byte_perm(kk[c].w, 0, 0x1032);
            uint4* dst = reinterpret_cast<uint4*>(smem + CV_BASE + c * CV_CH_BYTES + CV_XT_BYTES + (16 + 8 * u) * 4);
            dst[0] = lo; dst[1] = hi;
        }
        fence_proxy_async();
        __syncwarp();
        asm volatile("bar.arrive 2, 512;" ::: "memory");
        cluster_wait();
        if (u == 32) {
            const CUtensorMap* mw = rank ? &map_u : &map_g;
            for (int it = 0; it < PRE; it++) {
                mbar_expect_tx(barFull + 8 * it, SLOT);
                tma_load_2d_mc(sb + it * SLOT + rank * 8192, mw, barFull + 8 * it, f0, 64 * it, (uint16_t)3);
            }
        }
        asm volatile("bar.sync 3, 256;" ::: "memory");
    }
    TS(0, 1, tid == 0);
    mbar_wait(barKV, 0);
    fence_proxy_async();
    if (tid < 256) asm volatile("bar.sync 2, 512;" ::: "memory");

    const int wg = __shfl_sync(0xffffffffu, tid >> 7, 0);
    {
        const int wq = warp & 3, g = lane >> 2, t = lane & 3;
        uint8_t* chs = smem + CV_BASE + wg * CV_CH_BYTES;
        float acc[64];
#pragma unroll
        for (int i = 0; i < 64; i++) acc[i] = 0.f;
        const uint32_t* wp = reinterpret_cast<const uint32_t*>(chs + CV_XT_BYTES) + 16 + 16 * wq + g - 2 * t;
        conv_mma(acc, wp, smem_u32(chs));
        TS(0, 4 + wg, (tid & 127) == 0);
        if (wg < 2) {
            if (tid == 0) {
                unsigned int v;
                asm volatile("ld.acquire.gpu.global.u32 %0, [%1];" : "=r"(v) : "l"(&g_bar) : "memory");
                const unsigned int target = *reinterpret_cast<volatile unsigned int*>(smem + ONES_OFF + 256);
                for (unsigned int it = 0; (int)(v - target) < 0 && it < (1u << 22); it++) asm volatile("ld.acquire.gpu.global.u32 %0, [%1];" : "=r"(v) : "l"(&g_bar) : "memory");
                fence_proxy_async_global();
                mbar_expect_tx(barXS, 8192);
                asm volatile("cp.async.bulk.shared::cluster.global.mbarrier::complete_tx::bytes [%0], [%1], %2, [%3];"
                             ::"r"(sb + CV_ST_OFF), "l"(g_stats), "r"(8192), "r"(barXS) : "memory");
                constexpr int SH = D_ * F_ * 2 / 128;
                asm volatile("cp.async.bulk.prefetch.L2.global [%0], %1;" ::"l"(reinterpret_cast<const uint8_t*>(w_gate) + (size_t)bid * SH), "r"(SH) : "memory");
                asm volatile("cp.async.bulk.prefetch.L2.global [%0], %1;" ::"l"(reinterpret_cast<const uint8_t*>(w_up) + (size_t)bid * SH), "r"(SH) : "memory");
                asm volatile("cp.async.bulk.prefetch.L2.global [%0], %1;" ::"l"(reinterpret_cast<const uint8_t*>(w_down) + (size_t)bid * SH), "r"(SH) : "memory");
            }
            __syncwarp();
        }
        {
            const uint32_t dbase = mapa(sb, g >> 2);
            mbar_wait(barXin, 0);
#pragma unroll 1
            for (int i = 0; i < 2; i++) {
                const int row0 = 32 * warp + 512 * i;
                uint32_t c[4];
                load_chunk_t(sb + CV_XI_OFF + row0 * 16, lane, c);
                const int p = 128 * rank + (row0 >> 3) + t;
                st_async_v4(dbase + CV_XS_OFF + (g & 3) * CV_XS_PITCH + p * 16, c, dbase + BAR_OFF + (barXS - barFull));
            }
            if (wg == 2) asm volatile("bar.sync 10, 512;" ::: "memory");
            else asm volatile("bar.arrive 10, 512;" ::: "memory");
        }
        const uint32_t pbase = smem_u32(chs + CV_XT_BYTES + CV_WT_BYTES + (wq & 1) * CV_P_BYTES);
        uint32_t pa[4];
        bool ok0[4];
#pragma unroll
        for (int e = 0; e < 4; e++) {
            const int s = 16 * (127 - 2 * t) + 16 * wq + g - 16 * (e & 1) + 8 * (e >> 1);
            pa[e] = pbase + (s + 4 * (s >> 3)) * 4;
            ok0[e] = s < S_;
        }
        if (wq < 2) {
#pragma unroll
            for (int i = 0; i < 64; i++) {
                const int e = (i & 1) | (i & 2);
                if (i >= 4 || ok0[e]) asm volatile("st.shared.f32 [%0], %1;" ::"r"(pa[e] - 768 * (i >> 2)), "f"(acc[i]) : "memory");
            }
            if (wq == 1 && lane < 16) asm volatile("st.shared.f32 [%0], %1;" ::"r"(pbase + (lane + 4 * (lane >> 3)) * 4), "f"(0.f) : "memory");
        }
        asm volatile("bar.sync %0, 128;" ::"r"(6 + wg) : "memory");
        if (wq >= 2) {
#pragma unroll
            for (int i0 = 0; i0 < 64; i0 += 16) {
                float o[16];
#pragma unroll
                for (int i = i0; i < i0 + 16; i++) {
                    const int e = (i & 1) | (i & 2);
                    o[i - i0] = 0.f;
                    if (i >= 4 || ok0[e]) asm volatile("ld.shared.f32 %0, [%1];" : "=f"(o[i - i0]) : "r"(pa[e] - 768 * (i >> 2)));
                }
#pragma unroll
                for (int i = i0; i < i0 + 16; i++) {
                    const int e = (i & 1) | (i & 2);
                    if (i >= 4 || ok0[e]) asm volatile("st.shared.f32 [%0], %1;" ::"r"(pa[e] - 768 * (i >> 2)), "f"(o[i - i0] + acc[i]) : "memory");
                }
            }
        }
    }
    TS(0, 10, tid == 0);
    TS(0, 11, tid == 480);
    mbar_wait(barXS, 0);
    asm volatile("bar.sync %0, 128;" ::"r"(6 + wg) : "memory");
    TS(0, 8, tid == 0);
    {
        const int c = wg, lt = tid & 127;
        const uint8_t* cb = smem + CV_BASE + c * CV_CH_BYTES;
        const uint32_t dw = (c & 2) ? dD.y : dD.x;
        const float Dv = (c & 1) ? bf_hi(dw) : bf_lo(dw);
#pragma unroll 1
        for (int it = 0; it < 2; it++) {
            const int p = lt + 128 * it;
            const int s0 = 8 * p;
            const float4* p0 = reinterpret_cast<const float4*>(cb + CV_XT_BYTES + CV_WT_BYTES + p * 48);
            const float4* p1 = reinterpret_cast<const float4*>(cb + CV_XT_BYTES + CV_WT_BYTES + CV_P_BYTES + p * 48);
            const uint4 kv = *reinterpret_cast<const uint4*>(cb + ((p & 1) * CV_R + 127 - (p >> 1)) * 16);
            const uint4 xv = *reinterpret_cast<const uint4*>(smem + CV_XS_OFF + c * CV_XS_PITCH + p * 16);
            const uint4 sa_ = *reinterpret_cast<const uint4*>(smem + CV_ST_OFF + s0 * 4), sb_ = *reinterpret_cast<const uint4*>(smem + CV_ST_OFF + s0 * 4 + 16);
            const uint32_t sw_[8] = {sa_.x, sa_.y, sa_.z, sa_.w, sb_.x, sb_.y, sb_.z, sb_.w};
            const float4 a0 = p0[0], a1 = p0[1], b0 = p1[0], b1 = p1[1];
            float y[8] = {a0.x + b0.x, a0.y + b0.y, a0.z + b0.z, a0.w + b0.w, a1.x + b1.x, a1.y + b1.y, a1.z + b1.z, a1.w + b1.w};
            const uint32_t kw[4] = {kv.x, kv.y, kv.z, kv.w};
            const uint32_t xw[4] = {xv.x, xv.y, xv.z, xv.w};
            uint32_t ow[4];
#pragma unroll
            for (int j = 0; j < 4; j++) {
                float e0 = bf_lo(kw[j]) * Dv, e1 = bf_hi(kw[j]) * Dv;
                bf16r2(e0, e1);
                bf16r2(y[2 * j], y[2 * j + 1]);
                const uint32_t zp = pack_bf16(y[2 * j] + e0, y[2 * j + 1] + e1);
                float q0 = bf_lo(xw[j]) - bf_lo(sw_[2 * j]), q1 = bf_hi(xw[j]) - bf_lo(sw_[2 * j + 1]);
                bf16r2(q0, q1);
                const uint32_t qp = pack_bf16(__fdividef(q0, bf_hi(sw_[2 * j])), __fdividef(q1, bf_hi(sw_[2 * j + 1])));
                const bf162 qz = __hmul2_rn(*reinterpret_cast<const bf162*>(&qp), *reinterpret_cast<const bf162*>(&zp));
                const bf162 hv = __hadd2_rn(*reinterpret_cast<const bf162*>(&xw[j]), qz);
                ow[j] = *reinterpret_cast<const uint32_t*>(&hv);
            }
            TS(0, 13, tid == 0 && it == 0);
            asm volatile("st.global.v4.u32 [%0], {%1,%2,%3,%4};" ::"l"(g_hb + (size_t)(p >> 1) * (D_ * 16) + (d0 + c) * 16 + ((p & 1) ^ rank) * 8),
                         "r"(ow[0]), "r"(ow[1]), "r"(ow[2]), "r"(ow[3]) : "memory");
            TS(0, 14, tid == 0 && it == 0);
        }
    }
    TS(0, 12, tid == 0);
    asm volatile("bar.sync %0, 128;" ::"r"(6 + wg) : "memory");
    if ((tid & 127) == 96) {
        __threadfence();
        atomicAdd(&g_c1, 1u);
    }
    fence_proxy_async();
    __syncthreads();
    TS(0, 9, tid == 0);

    if (wg >= 2) {
        asm volatile("setmaxnreg.dec.sync.aligned.u32 24;");
        if (warp == 12 || warp == 13) {
            for (int T = 0; T < 4; T++) {
                asm volatile("bar.sync %0, 160;" ::"r"(warp - 1) : "memory");
                if (lane == 0) {
                    __threadfence();
                    atomicAdd(&g_c2[(mt1 * 2 + (ns >> 2)) * 4 + T], 1u);
                }
                __syncwarp();
            }
        }
        if (tid == 256) {
            for (int i = 0; i < 3; i++) {
                const uint32_t e = barEmpty + 8 * (PRE + i);
                asm volatile("mbarrier.arrive.shared::cta.b64 _, [%0], 2;" ::"r"(e) : "memory");
                asm volatile("mbarrier.arrive.shared::cluster.b64 _, [%0], 2;" ::"r"(mapa(e, rank ^ 1)) : "memory");
            }
            wait_counter(&g_c1, 512u);
            fence_proxy_async_global();
            TS(1, 11, true);
            for (int i = 0; i < 8; i++) {
                mbar_expect_tx(barA + 8 * i, 16384);
                asm volatile("cp.async.bulk.shared::cluster.global.mbarrier::complete_tx::bytes [%0], [%1], %2, [%3];"
                             ::"r"(sb + (A_SLOT0 + i) * SLOT), "l"(g_hb + (size_t)(mt1 * 8 + i) * (D_ * 16)), "r"(16384), "r"(barA + 8 * i) : "memory");
            }
            for (int T = 0; T < 2; T++) wait_counter(&g_c2[(2 * mt2 + rank) * 4 + T], 8u);
            fence_proxy_async_global();
            mbar_wait(barG1, 0);
            for (int j = 0; j < 14; j++) {
                const int st = g2_slotA(j), f = g2_fillA(j);
                if (j == 8 || j == 12) {
                    wait_counter(&g_c2[(2 * mt2 + rank) * 4 + (j >> 2)], 8u);
                    fence_proxy_async_global();
                }
                if (j < NA) mbar_wait(barEmpty + 8 * st, (f - (st < PRE ? 1 : 0)) & 1);
                else mbar_wait(barAE + 8 * (j % NA), (j / NA - 1) & 1);
                mbar_expect_tx(barFull + 8 * st, SLOT);
                asm volatile("cp.async.bulk.shared::cluster.global.mbarrier::complete_tx::bytes [%0], [%1], %2, [%3];"
                             ::"r"(sb + st * SLOT), "l"(reinterpret_cast<const uint8_t*>(g_hh) + ((size_t)mt2 * 28 + rank * 14 + j) * 16384), "r"(16384), "r"(barFull + 8 * st) : "memory");
            }
        } else if (tid == 288) {
            const CUtensorMap* mw = rank ? &map_u : &map_g;
            for (int it = PRE; it < 32; it++) {
                const int st = it % NSLOT, f = it / NSLOT;
                mbar_wait(barEmpty + 8 * st, (f - (st < PRE ? 1 : 0)) & 1);
                if (it < 24) {
                    mbar_expect_tx(barFull + 8 * st, SLOT);
                    tma_load_2d_mc(sb + st * SLOT + rank * 8192, mw, barFull + 8 * st, f0 + 64 * (it >> 3), 64 * (it & 7), (uint16_t)3);
                } else {
                    mbar_expect_tx(barFull + 8 * st, SLOT / 2);
                    tma_load_2d_mc(sb + st * SLOT + rank * 4096, rank ? &map_u32 : &map_g32, barFull + 8 * st, f0 + 192, 64 * (it & 7), (uint16_t)3);
                }
            }
            mbar_arrive(barG1);
            const int c0 = nt * 128, k0 = rank * 896;
            for (int j = 0; j < 14; j++) {
                const int st = g2_slotB(j), f = g2_fillB(j);
                mbar_wait(barEmpty + 8 * st, (f - (st < PRE ? 1 : 0)) & 1);
                mbar_expect_tx(barFull + 8 * st, SLOT);
                if (j < 12) {
                    const int kr = k0 + 224 * (j & 3) + 64 * (j >> 2);
                    tma_load_2d(sb + st * SLOT, &map_d, barFull + 8 * st, c0, kr);
                    tma_load_2d(sb + st * SLOT + 8192, &map_d, barFull + 8 * st, c0 + 64, kr);
                } else {
                    const int kr = k0 + 448 * (j - 12) + 192;
                    tma_load_2d(sb + st * SLOT, &map_d32, barFull + 8 * st, c0, kr);
                    tma_load_2d(sb + st * SLOT + 4096, &map_d32, barFull + 8 * st, c0, kr + 224);
                    tma_load_2d(sb + st * SLOT + 8192, &map_d32, barFull + 8 * st, c0 + 64, kr);
                    tma_load_2d(sb + st * SLOT + 12288, &map_d32, barFull + 8 * st, c0 + 64, kr + 224);
                }
            }
        }
    } else {
        asm volatile("setmaxnreg.inc.sync.aligned.u32 232;");
        const int row1 = mt1 * 128;
        {
            uint32_t a[32][4];
            {
                const uint32_t abase = sb + (A_SLOT0 + warp) * SLOT + ((lane & 7) + 8 * (lane >> 4)) * 32 + (((lane >> 3) ^ (lane >> 2)) & 1) * 16;
                mbar_wait(barA + 8 * warp, 0);
                TS(1, 12, tid == 0);
#pragma unroll
                for (int kk = 0; kk < 32; kk++) {
                    asm volatile("ldmatrix.sync.aligned.m8n8.x4.trans.shared.b16 {%0,%1,%2,%3}, [%4];"
                                 : "=r"(a[kk][0]), "=r"(a[kk][1]), "=r"(a[kk][2]), "=r"(a[kk][3])
                                 : "r"(abase + kk * 512) : "memory");
                }
            }
            TS(1, 14, tid == 0);
            float inv0, inv1;
            {
                float rs[4] = {0.f, 0.f, 0.f, 0.f};
                const uint64_t dones = make_desc(sb + ONES_OFF, 128, 128, 0);
                wgmma_fence();
#pragma unroll
                for (int kk = 0; kk < 32; kk++) wgmma_rs_n8<0>(rs, a[kk][0], a[kk][1], a[kk][2], a[kk][3], (uint32_t)dones, (uint32_t)(dones >> 32));
                wgmma_commit();
                float ga = 0.f, gb = 0.f, gc = 0.f, gd = 0.f;
#pragma unroll
                for (int kk = 0; kk < 32; kk++) {
                    float l, h;
                    l = bf_lo(a[kk][0]); h = bf_hi(a[kk][0]); ga += l * l; gc += h * h;
                    l = bf_lo(a[kk][2]); h = bf_hi(a[kk][2]); ga += l * l; gc += h * h;
                    l = bf_lo(a[kk][1]); h = bf_hi(a[kk][1]); gb += l * l; gd += h * h;
                    l = bf_lo(a[kk][3]); h = bf_hi(a[kk][3]); gb += l * l; gd += h * h;
                }
                ga += gc; gb += gd;
                ga += __shfl_xor_sync(0xffffffffu, ga, 1); ga += __shfl_xor_sync(0xffffffffu, ga, 2);
                gb += __shfl_xor_sync(0xffffffffu, gb, 1); gb += __shfl_xor_sync(0xffffffffu, gb, 2);
                wgmma_wait<0>();
                if (lane == 0) {
                    const uint32_t e = barEmpty + 8 * (A_SLOT0 + warp);
                    asm volatile("mbarrier.arrive.shared::cta.b64 _, [%0], 2;" ::"r"(e) : "memory");
                    asm volatile("mbarrier.arrive.shared::cluster.b64 _, [%0], 2;" ::"r"(mapa(e, rank ^ 1)) : "memory");
                }
                const float mean0 = rs[0] * (1.f / 512.f), mean1 = rs[2] * (1.f / 512.f);
                const uint32_t mp = pack_bf16(mean0, mean1);
                const uint32_t m0 = __byte_perm(mp, 0, 0x1010), m1 = __byte_perm(mp, 0, 0x3232);
#pragma unroll
                for (int kk = 0; kk < 32; kk++) {
#pragma unroll
                    for (int r = 0; r < 4; r++) {
                        const uint32_t mm = (r & 1) ? m1 : m0;
                        const bf162 dd = __hsub2_rn(*reinterpret_cast<const bf162*>(&a[kk][r]), *reinterpret_cast<const bf162*>(&mm));
                        a[kk][r] = *reinterpret_cast<const uint32_t*>(&dd);
                    }
                }
                const float v0 = fmaxf(ga * (1.f / 512.f) - mean0 * mean0, 0.f), v1 = fmaxf(gb * (1.f / 512.f) - mean1 * mean1, 0.f);
                inv0 = __fdividef(1.f, bf16r(sqrtf(bf16r(bf16r(v0) + 1e-5f))));
                inv1 = __fdividef(1.f, bf16r(sqrtf(bf16r(bf16r(v1) + 1e-5f))));
            }
            TS(1, 2, tid == 0);
            if (wg == 1) asm volatile("bar.sync 5, 256;" ::: "memory");
#pragma unroll 1
            for (int T = 0; T < 3; T++) gemm1_pass<true>(T, a, inv0, inv1, sb, rank ^ 1, row1, ns, tid, wg);
            gemm1_pass<false>(3, a, inv0, inv1, sb, rank ^ 1, row1, ns, tid, wg);
        }
        TS(2, 0, tid == 0);

        {
        uint32_t sb_, tid_;
        asm volatile("mov.u32 %0, %1;" : "=r"(sb_) : "r"(sb) : "memory");
        asm volatile("mov.u32 %0, %%tid.x;" : "=r"(tid_) :: "memory");
        const uint32_t sb = sb_;
        const int tid = (int)tid_, warp = tid >> 5, lane = tid & 31;
        const uint32_t barFull = sb + BAR_OFF, barEmpty = barFull + 8 * NSLOT, barA = barEmpty + 8 * NSLOT;
        const uint32_t barX = barA + 64 + 16, barAE = barX + 24, barRdy = barAE + 56;
        const int c0 = nt * 128, row2 = mt2 * 128;
        float acc[64];
#pragma unroll
        for (int i = 0; i < 64; i++) acc[i] = 0.f;
        {
            uint32_t a[2][4][4];
            const uint64_t d0_ = make_desc(sb, 8192, 1024, 1);
            const uint32_t dlo0 = (uint32_t)d0_, dhi = (uint32_t)(d0_ >> 32);
            const uint32_t abase = sb + warp * 2048 + lane * 16;
#pragma unroll
            for (int j = 0; j < 14; j++) {
                const int jj = j & 1;
                const int sa = g2_slotA(j), sbk = g2_slotB(j);
                mbar_wait(barFull + 8 * sa, g2_fillA(j) & 1);
                if (j >= 2) {
                    wgmma_wait<1>();
                    if (j < 8 && (tid & 127) == 0) asm volatile("mbarrier.arrive.shared::cta.b64 _, [%0], 2;" ::"r"(barEmpty + 8 * g2_slotB(j - 2)) : "memory");
                    if (j == 9 && (tid & 127) == 0) mbar_arrive_cluster(mapa(barRdy, rank ^ 1));
                }
#pragma unroll
                for (int kk = 0; kk < 4; kk++)
                    asm volatile("ld.shared.v4.u32 {%0,%1,%2,%3}, [%4];" : "=r"(a[jj][kk][0]), "=r"(a[jj][kk][1]), "=r"(a[jj][kk][2]), "=r"(a[jj][kk][3])
                                 : "r"(abase + sa * SLOT + kk * 512) : "memory");
                mbar_wait(barFull + 8 * sbk, g2_fillB(j) & 1);
                if ((j & 1) == 0) TS(2, 5 + (j >> 1), tid == 128);
                wgmma_fence();
                const uint32_t dlo = dlo0 + sbk * (SLOT / 16);
                wgmma_rst_n128<0>(acc, a[jj][0], dlo, dhi); wgmma_rst_n128<128>(acc, a[jj][1], dlo, dhi);
                wgmma_rst_n128<256>(acc, a[jj][2], dlo, dhi); wgmma_rst_n128<384>(acc, a[jj][3], dlo, dhi);
                wgmma_commit();
                if (j < 14 - NA) {
                    __syncwarp();
                    if (lane == 0) asm volatile("mbarrier.arrive.shared::cta.b64 _, [%0];" ::"r"(barAE + 8 * (j % NA)) : "memory");
                }
            }
        }
        uint4 hv[4];
        {
            const uint4* hsrc = reinterpret_cast<const uint4*>(g_hb + (size_t)(mt2 * 8 + warp) * (D_ * 16) + (c0 + 64 * rank) * 16);
#pragma unroll
            for (int i = 0; i < 4; i++) hv[i] = __ldcg(hsrc + lane + 32 * i);
        }
        wgmma_wait<0>();
        TS(2, 1 + wg, (tid & 127) == 0);
        {
            const uint32_t dst = mapa(sb + X_OFF + tid * 16, rank ^ 1);
            const uint32_t dbar = mapa(barX, rank ^ 1);
            mbar_wait(barRdy, 0);
#pragma unroll
            for (int j = 0; j < 8; j++) {
                uint32_t v[4];
#pragma unroll
                for (int e = 0; e < 4; e++) v[e] = __float_as_uint(rank == 0 ? acc[32 + 4 * j + e] : acc[4 * j + e]);
                st_async_v4(dst + j * 4096, v, dbar);
            }
        }
        asm volatile("bar.sync 4, 256;" ::: "memory");
        const uint32_t stg = sb + warp * 2048;
#pragma unroll
        for (int i = 0; i < 4; i++)
            asm volatile("st.shared.v4.u32 [%0], {%1,%2,%3,%4};" ::"r"(stg + (lane + 32 * i) * 16), "r"(hv[i].x), "r"(hv[i].y), "r"(hv[i].z), "r"(hv[i].w) : "memory");
        __syncwarp();
        uint32_t hf_[8][2];
#pragma unroll
        for (int j = 0; j < 8; j += 2) {
            asm volatile("ldmatrix.sync.aligned.m8n8.x4.trans.shared.b16 {%0,%1,%2,%3}, [%4];"
                         : "=r"(hf_[j][0]), "=r"(hf_[j][1]), "=r"(hf_[j + 1][0]), "=r"(hf_[j + 1][1])
                         : "r"(stg + (8 * j + (lane & 7) + 8 * (lane >> 4)) * 32 + (((lane >> 3) ^ (lane >> 2)) & 1) * 16) : "memory");
        }
        __syncwarp();
        mbar_wait(barX, 0);
        uint32_t po[8][2];
#pragma unroll
        for (int j = 0; j < 8; j++) {
            float4 v;
            asm volatile("ld.shared.v4.f32 {%0,%1,%2,%3}, [%4];" : "=f"(v.x), "=f"(v.y), "=f"(v.z), "=f"(v.w) : "r"(sb + X_OFF + tid * 16 + j * 4096));
            float o0, o1, o2, o3;
            if (rank == 0) { o0 = acc[4 * j] + v.x; o1 = acc[4 * j + 1] + v.y; o2 = acc[4 * j + 2] + v.z; o3 = acc[4 * j + 3] + v.w; }
            else { o0 = acc[32 + 4 * j] + v.x; o1 = acc[33 + 4 * j] + v.y; o2 = acc[34 + 4 * j] + v.z; o3 = acc[35 + 4 * j] + v.w; }
            bf16r2(o0, o1); bf16r2(o2, o3);
            po[j][0] = pack_bf16(bf_lo(hf_[j][0]) + o0, bf_hi(hf_[j][0]) + o1);
            po[j][1] = pack_bf16(bf_lo(hf_[j][1]) + o2, bf_hi(hf_[j][1]) + o3);
        }
        const int mi = lane >> 3, rr = lane & 7;
#pragma unroll
        for (int j = 0; j < 8; j += 2) {
            const int row = rr + 8 * (mi & 1);
            const int chunk = j + (mi >> 1);
            stmatrix_x4(stg + row * 128 + ((chunk ^ (row & 7)) * 16), po[j][0], po[j][1], po[j + 1][0], po[j + 1][1]);
        }
        __syncwarp();
        const size_t obase = (size_t)(row2 + 16 * warp) * D_ + c0 + 64 * rank;
#pragma unroll
        for (int i = 0; i < 4; i++) {
            const int row = 4 * i + (lane >> 3), chunk = lane & 7;
            uint4 v;
            asm volatile("ld.shared.v4.u32 {%0,%1,%2,%3}, [%4];" : "=r"(v.x), "=r"(v.y), "=r"(v.z), "=r"(v.w) : "r"(stg + row * 128 + ((chunk ^ (row & 7)) * 16)));
            *reinterpret_cast<uint4*>(out + obase + (size_t)row * D_ + chunk * 8) = v;
        }
        TS(2, 3 + wg, (tid & 127) == 0);
        if (warp == 0) {
            unsigned int last = 0;
            if (lane == 0) last = (atomicAdd(&g_c3, 1u) == 127u);
            last = __shfl_sync(0xffffffffu, last, 0);
            if (last) {
                reinterpret_cast<uint4*>(g_c2)[lane] = make_uint4(0u, 0u, 0u, 0u);
                if (lane == 0) { g_c1 = 0u; g_c3 = 0u; }
            }
        }
        }
    }
}

typedef CUresult (*PFN_encodeTiled)(CUtensorMap*, CUtensorMapDataType, cuuint32_t, void*, const cuuint64_t*, const cuuint64_t*,
                                    const cuuint32_t*, const cuuint32_t*, CUtensorMapInterleave, CUtensorMapSwizzle,
                                    CUtensorMapL2promotion, CUtensorMapFloatOOBfill);

static void make_map(PFN_encodeTiled enc, CUtensorMap* m, const void* ptr, uint64_t inner, uint64_t outer, uint32_t box_inner, uint32_t box_outer,
                     CUtensorMapSwizzle swz = CU_TENSOR_MAP_SWIZZLE_128B) {
    cuuint64_t dims[2] = {inner, outer};
    cuuint64_t strides[1] = {inner * 2};
    cuuint32_t box[2] = {box_inner, box_outer};
    cuuint32_t es[2] = {1, 1};
    enc(m, CU_TENSOR_MAP_DATA_TYPE_BFLOAT16, 2, const_cast<void*>(ptr), dims, strides, box, es, CU_TENSOR_MAP_INTERLEAVE_NONE,
        swz, CU_TENSOR_MAP_L2_PROMOTION_L2_256B, CU_TENSOR_MAP_FLOAT_OOB_FILL_NONE);
}

extern "C" void kernel_launch(void* const* d_in, const int* in_sizes, int n_in, void* d_out, int out_size) {
    const bf16* A_q = (const bf16*)d_in[0];
    const bf16* A_k = (const bf16*)d_in[1];
    const bf16* A_v = (const bf16*)d_in[2];
    const bf16* A_shift = (const bf16*)d_in[3];
    const bf16* A_ssmk = (const bf16*)d_in[4];
    const bf16* A_ssmD = (const bf16*)d_in[5];
    const bf16* w_gate = (const bf16*)d_in[7];
    const bf16* w_up = (const bf16*)d_in[8];
    const bf16* w_down = (const bf16*)d_in[9];

    static bool init = false;
    static CUtensorMap map_g, map_u, map_g32, map_u32, map_d, map_d32, map_k, map_kh, map_v, map_x;
    static const void* cached[6] = {nullptr, nullptr, nullptr, nullptr, nullptr, nullptr};
    if (!init || cached[0] != w_gate || cached[1] != w_up || cached[2] != w_down || cached[3] != A_q || cached[4] != A_k || cached[5] != A_v) {
        void* fn = nullptr;
        cudaDriverEntryPointQueryResult qres;
        cudaGetDriverEntryPoint("cuTensorMapEncodeTiled", &fn, cudaEnableDefault, &qres);
        PFN_encodeTiled enc = (PFN_encodeTiled)fn;
        make_map(enc, &map_g, w_gate, F_, D_, 64, 64);
        make_map(enc, &map_u, w_up, F_, D_, 64, 64);
        make_map(enc, &map_g32, w_gate, F_, D_, 32, 64, CU_TENSOR_MAP_SWIZZLE_64B);
        make_map(enc, &map_u32, w_up, F_, D_, 32, 64, CU_TENSOR_MAP_SWIZZLE_64B);
        make_map(enc, &map_d, w_down, D_, F_, 64, 64);
        make_map(enc, &map_d32, w_down, D_, F_, 64, 32);
        make_map(enc, &map_k, A_k, D_, S_, 8, 256, CU_TENSOR_MAP_SWIZZLE_NONE);
        make_map(enc, &map_kh, A_k, D_, S_, 8, 8, CU_TENSOR_MAP_SWIZZLE_NONE);
        make_map(enc, &map_v, A_v, D_, S_, 8, 256, CU_TENSOR_MAP_SWIZZLE_NONE);
        make_map(enc, &map_x, A_q, D_, S_, 8, 256, CU_TENSOR_MAP_SWIZZLE_NONE);
        cudaFuncSetAttribute(mega_kernel, cudaFuncAttributeMaxDynamicSharedMemorySize, SMEM_BYTES);
        cached[0] = w_gate; cached[1] = w_up; cached[2] = w_down; cached[3] = A_q; cached[4] = A_k; cached[5] = A_v;
        init = true;
    }
    mega_kernel<<<128, 512, SMEM_BYTES, cudaStreamPerThread>>>(A_q, A_k, A_v, A_shift, A_ssmk, A_ssmD, w_gate, w_up, w_down, (bf16*)d_out,
                                                               map_g, map_u, map_g32, map_u32, map_d, map_d32, map_k, map_kh, map_v, map_x);
}
```

```cpp
#include <cuda_runtime.h>
#include <cuda_bf16.h>
#include <cuda.h>
#include <stdint.h>

typedef __nv_bfloat16 bf16;
typedef __nv_bfloat162 bf162;

constexpr int S_ = 2048, D_ = 512, F_ = 1792;

__device__ __align__(1024) bf16 g_hb[S_ * D_];
__device__ __align__(1024) bf16 g_hh[S_ * F_];
__device__ __align__(128) uint32_t g_stats[S_];
__device__ unsigned int g_bar;
__device__ unsigned int g_c1;
__device__ __align__(16) unsigned int g_c2[128];
__device__ unsigned int g_c3;

#define TS_INIT()
#define TS_DUMP()
#define TS(k, i, cond)

__device__ __forceinline__ uint32_t smem_u32(const void* p) { return (uint32_t)__cvta_generic_to_shared(p); }

__device__ __forceinline__ void mbar_init(uint32_t bar, uint32_t count) {
    asm volatile("mbarrier.init.shared::cta.b64 [%0], %1;" ::"r"(bar), "r"(count) : "memory");
}
__device__ __forceinline__ void mbar_expect_tx(uint32_t bar, uint32_t bytes) {
    asm volatile("mbarrier.arrive.expect_tx.shared::cta.b64 _, [%0], %1;" ::"r"(bar), "r"(bytes) : "memory");
}
__device__ __forceinline__ void mbar_arrive(uint32_t bar) {
    asm volatile("mbarrier.arrive.shared::cta.b64 _, [%0];" ::"r"(bar) : "memory");
}
__device__ __forceinline__ uint32_t mapa(uint32_t addr, uint32_t rank) {
    uint32_t r;
    asm volatile("mapa.shared::cluster.u32 %0, %1, %2;" : "=r"(r) : "r"(addr), "r"(rank));
    return r;
}
__device__ __forceinline__ void mbar_arrive_cluster(uint32_t cluster_addr) {
    asm volatile("mbarrier.arrive.shared::cluster.b64 _, [%0];" ::"r"(cluster_addr) : "memory");
}
__device__ __forceinline__ void mbar_wait(uint32_t bar, uint32_t parity) {
    asm volatile(
        "{\n.reg .pred p;\n.reg .u32 c;\n"
        "mov.u32 c, 0;\n"
        "WAIT_%=:\n"
        "mbarrier.try_wait.parity.shared::cta.b64 p, [%0], %1;\n"
        "@p bra DONE_%=;\n"
        "add.u32 c, c, 1;\n"
        "setp.lt.u32 p, c, 4194304;\n"
        "@p bra WAIT_%=;\n"
        "DONE_%=:\n}\n"
        ::"r"(bar), "r"(parity) : "memory");
}
__device__ __forceinline__ void wait_counter(const unsigned int* p, unsigned int target) {
    unsigned int v, it = 0;
    do {
        asm volatile("ld.acquire.gpu.global.u32 %0, [%1];" : "=r"(v) : "l"(p) : "memory");
        if (++it > (1u << 24)) break;
    } while (v < target);
}
__device__ __forceinline__ void cluster_arrive() { asm volatile("barrier.cluster.arrive.release.aligned;" ::: "memory"); }
__device__ __forceinline__ void cluster_wait() { asm volatile("barrier.cluster.wait.acquire.aligned;" ::: "memory"); }
__device__ __forceinline__ void fence_proxy_async() { asm volatile("fence.proxy.async.shared::cta;" ::: "memory"); }
__device__ __forceinline__ void fence_proxy_async_global() { asm volatile("fence.proxy.async.global;" ::: "memory"); }
__device__ __forceinline__ void wgmma_fence() { asm volatile("wgmma.fence.sync.aligned;" ::: "memory"); }
__device__ __forceinline__ void wgmma_commit() { asm volatile("wgmma.commit_group.sync.aligned;" ::: "memory"); }
template <int N> __device__ __forceinline__ void wgmma_wait() { asm volatile("wgmma.wait_group.sync.aligned %0;" ::"n"(N) : "memory"); }

__device__ __forceinline__ void tma_load_2d(uint32_t dst, const CUtensorMap* map, uint32_t bar, int c0, int c1) {
    asm volatile(
        "cp.async.bulk.tensor.2d.shared::cluster.global.mbarrier::complete_tx::bytes [%0], [%1, {%3, %4}], [%2];"
        ::"r"(dst), "l"(map), "r"(bar), "r"(c0), "r"(c1) : "memory");
}
__device__ __forceinline__ void tma_load_2d_mc(uint32_t dst, const CUtensorMap* map, uint32_t bar, int c0, int c1, uint16_t mask) {
    asm volatile(
        "cp.async.bulk.tensor.2d.shared::cluster.global.mbarrier::complete_tx::bytes.multicast::cluster [%0], [%1, {%3, %4}], [%2], %5;"
        ::"r"(dst), "l"(map), "r"(bar), "r"(c0), "r"(c1), "h"(mask) : "memory");
}

__device__ __forceinline__ uint64_t make_desc(uint32_t addr, uint32_t lbo_bytes, uint32_t sbo_bytes, uint32_t swz) {
    uint64_t d = 0;
    d |= (uint64_t)((addr & 0x3FFFF) >> 4);
    d |= (uint64_t)((lbo_bytes & 0x3FFFF) >> 4) << 16;
    d |= (uint64_t)((sbo_bytes & 0x3FFFF) >> 4) << 32;
    d |= (uint64_t)swz << 62;
    return d;
}

__device__ __forceinline__ float bf16r(float x) { return __bfloat162float(__float2bfloat16_rn(x)); }
__device__ __forceinline__ uint32_t pack_bf16(float lo, float hi) {
    bf162 v = __floats2bfloat162_rn(lo, hi);
    return *reinterpret_cast<uint32_t*>(&v);
}
__device__ __forceinline__ float bf_lo(uint32_t u) { return __uint_as_float(u << 16); }
__device__ __forceinline__ float bf_hi(uint32_t u) { return __uint_as_float(u & 0xffff0000u); }
__device__ __forceinline__ void bf16r2(float& a, float& b) {
    const uint32_t p = pack_bf16(a, b);
    a = bf_lo(p); b = bf_hi(p);
}

__device__ __forceinline__ void stmatrix_x4(uint32_t addr, uint32_t r0, uint32_t r1, uint32_t r2, uint32_t r3) {
    asm volatile("stmatrix.sync.aligned.m8n8.x4.shared.b16 [%0], {%1,%2,%3,%4};" ::"r"(addr), "r"(r0), "r"(r1), "r"(r2), "r"(r3) : "memory");
}

template <int OFF>
__device__ __forceinline__ void wgmma_rs_n128(float* d, uint32_t a0, uint32_t a1, uint32_t a2, uint32_t a3, uint32_t dlo, uint32_t dhi) {
    asm volatile(
        "{\n.reg .b64 dsc;\n.reg .b32 lo;\nadd.s32 lo, %68, %70;\nmov.b64 dsc, {lo, %69};\n"
        "wgmma.mma_async.sync.aligned.m64n128k16.f32.bf16.bf16 "
        "{%0,%1,%2,%3,%4,%5,%6,%7,%8,%9,%10,%11,%12,%13,%14,%15,%16,%17,%18,%19,%20,%21,%22,%23,%24,%25,%26,%27,%28,%29,%30,%31,%32,%33,%34,%35,%36,%37,%38,%39,%40,%41,%42,%43,%44,%45,%46,%47,%48,%49,%50,%51,%52,%53,%54,%55,%56,%57,%58,%59,%60,%61,%62,%63}, {%64,%65,%66,%67}, dsc, 1, 1, 1, 0;\n}\n"
        : "+f"(d[0]), "+f"(d[1]), "+f"(d[2]), "+f"(d[3]), "+f"(d[4]), "+f"(d[5]), "+f"(d[6]), "+f"(d[7]), "+f"(d[8]), "+f"(d[9]), "+f"(d[10]), "+f"(d[11]), "+f"(d[12]), "+f"(d[13]), "+f"(d[14]), "+f"(d[15]), "+f"(d[16]), "+f"(d[17]), "+f"(d[18]), "+f"(d[19]), "+f"(d[20]), "+f"(d[21]), "+f"(d[22]), "+f"(d[23]), "+f"(d[24]), "+f"(d[25]), "+f"(d[26]), "+f"(d[27]), "+f"(d[28]), "+f"(d[29]), "+f"(d[30]), "+f"(d[31]), "+f"(d[32]), "+f"(d[33]), "+f"(d[34]), "+f"(d[35]), "+f"(d[36]), "+f"(d[37]), "+f"(d[38]), "+f"(d[39]), "+f"(d[40]), "+f"(d[41]), "+f"(d[42]), "+f"(d[43]), "+f"(d[44]), "+f"(d[45]), "+f"(d[46]), "+f"(d[47]), "+f"(d[48]), "+f"(d[49]), "+f"(d[50]), "+f"(d[51]), "+f"(d[52]), "+f"(d[53]), "+f"(d[54]), "+f"(d[55]), "+f"(d[56]), "+f"(d[57]), "+f"(d[58]), "+f"(d[59]), "+f"(d[60]), "+f"(d[61]), "+f"(d[62]), "+f"(d[63])
        : "r"(a0), "r"(a1), "r"(a2), "r"(a3), "r"(dlo), "r"(dhi), "n"(OFF));
}
template <int OFF>
__device__ __forceinline__ void wgmma_rs_n96(float* d, uint32_t a0, uint32_t a1, uint32_t a2, uint32_t a3, uint32_t dlo, uint32_t dhi) {
    asm volatile(
        "{\n.reg .b64 dsc;\n.reg .b32 lo;\nadd.s32 lo, %52, %54;\nmov.b64 dsc, {lo, %53};\n"
        "wgmma.mma_async.sync.aligned.m64n96k16.f32.bf16.bf16 "
        "{%0,%1,%2,%3,%4,%5,%6,%7,%8,%9,%10,%11,%12,%13,%14,%15,%16,%17,%18,%19,%20,%21,%22,%23,%24,%25,%26,%27,%28,%29,%30,%31,%32,%33,%34,%35,%36,%37,%38,%39,%40,%41,%42,%43,%44,%45,%46,%47}, {%48,%49,%50,%51}, dsc, 1, 1, 1, 0;\n}\n"
        : "+f"(d[0]), "+f"(d[1]), "+f"(d[2]), "+f"(d[3]), "+f"(d[4]), "+f"(d[5]), "+f"(d[6]), "+f"(d[7]), "+f"(d[8]), "+f"(d[9]), "+f"(d[10]), "+f"(d[11]), "+f"(d[12]), "+f"(d[13]), "+f"(d[14]), "+f"(d[15]), "+f"(d[16]), "+f"(d[17]), "+f"(d[18]), "+f"(d[19]), "+f"(d[20]), "+f"(d[21]), "+f"(d[22]), "+f"(d[23]), "+f"(d[24]), "+f"(d[25]), "+f"(d[26]), "+f"(d[27]), "+f"(d[28]), "+f"(d[29]), "+f"(d[30]), "+f"(d[31]), "+f"(d[32]), "+f"(d[33]), "+f"(d[34]), "+f"(d[35]), "+f"(d[36]), "+f"(d[37]), "+f"(d[38]), "+f"(d[39]), "+f"(d[40]), "+f"(d[41]), "+f"(d[42]), "+f"(d[43]), "+f"(d[44]), "+f"(d[45]), "+f"(d[46]), "+f"(d[47])
        : "r"(a0), "r"(a1), "r"(a2), "r"(a3), "r"(dlo), "r"(dhi), "n"(OFF));
}
template <int OFF>
__device__ __forceinline__ void wgmma_rs_n64(float* d, uint32_t a0, uint32_t a1, uint32_t a2, uint32_t a3, uint32_t dlo, uint32_t dhi) {
    asm volatile(
        "{\n.reg .b64 dsc;\n.reg .b32 lo;\nadd.s32 lo, %36, %38;\nmov.b64 dsc, {lo, %37};\n"
        "wgmma.mma_async.sync.aligned.m64n64k16.f32.bf16.bf16 "
        "{%0,%1,%2,%3,%4,%5,%6,%7,%8,%9,%10,%11,%12,%13,%14,%15,%16,%17,%18,%19,%20,%21,%22,%23,%24,%25,%26,%27,%28,%29,%30,%31}, {%32,%33,%34,%35}, dsc, 1, 1, 1, 0;\n}\n"
        : "+f"(d[0]), "+f"(d[1]), "+f"(d[2]), "+f"(d[3]), "+f"(d[4]), "+f"(d[5]), "+f"(d[6]), "+f"(d[7]), "+f"(d[8]), "+f"(d[9]), "+f"(d[10]), "+f"(d[11]), "+f"(d[12]), "+f"(d[13]), "+f"(d[14]), "+f"(d[15]), "+f"(d[16]), "+f"(d[17]), "+f"(d[18]), "+f"(d[19]), "+f"(d[20]), "+f"(d[21]), "+f"(d[22]), "+f"(d[23]), "+f"(d[24]), "+f"(d[25]), "+f"(d[26]), "+f"(d[27]), "+f"(d[28]), "+f"(d[29]), "+f"(d[30]), "+f"(d[31])
        : "r"(a0), "r"(a1), "r"(a2), "r"(a3), "r"(dlo), "r"(dhi), "n"(OFF));
}
template <int OFF>
__device__ __forceinline__ void wgmma_rs_n32(float* d, uint32_t a0, uint32_t a1, uint32_t a2, uint32_t a3, uint32_t dlo, uint32_t dhi) {
    asm volatile(
        "{\n.reg .b64 dsc;\n.reg .b32 lo;\nadd.s32 lo, %20, %22;\nmov.b64 dsc, {lo, %21};\n"
        "wgmma.mma_async.sync.aligned.m64n32k16.f32.bf16.bf16 "
        "{%0,%1,%2,%3,%4,%5,%6,%7,%8,%9,%10,%11,%12,%13,%14,%15}, {%16,%17,%18,%19}, dsc, 1, 1, 1, 0;\n}\n"
        : "+f"(d[0]), "+f"(d[1]), "+f"(d[2]), "+f"(d[3]), "+f"(d[4]), "+f"(d[5]), "+f"(d[6]), "+f"(d[7]), "+f"(d[8]), "+f"(d[9]), "+f"(d[10]), "+f"(d[11]), "+f"(d[12]), "+f"(d[13]), "+f"(d[14]), "+f"(d[15])
        : "r"(a0), "r"(a1), "r"(a2), "r"(a3), "r"(dlo), "r"(dhi), "n"(OFF));
}
template <int OFF>
__device__ __forceinline__ void wgmma_rs_n8(float* d, uint32_t a0, uint32_t a1, uint32_t a2, uint32_t a3, uint32_t dlo, uint32_t dhi) {
    asm volatile(
        "{\n.reg .b64 dsc;\n.reg .b32 lo;\nadd.s32 lo, %8, %10;\nmov.b64 dsc, {lo, %9};\n"
        "wgmma.mma_async.sync.aligned.m64n8k16.f32.bf16.bf16 "
        "{%0,%1,%2,%3}, {%4,%5,%6,%7}, dsc, 1, 1, 1, 0;\n}\n"
        : "+f"(d[0]), "+f"(d[1]), "+f"(d[2]), "+f"(d[3])
        : "r"(a0), "r"(a1), "r"(a2), "r"(a3), "r"(dlo), "r"(dhi), "n"(OFF));
}
template <int OFF>
__device__ __forceinline__ void wgmma_rst_n128(float* d, const uint32_t* a, uint32_t dlo, uint32_t dhi) {
    asm volatile(
        "{\n.reg .b64 dsc;\n.reg .b32 lo;\nadd.s32 lo, %68, %70;\nmov.b64 dsc, {lo, %69};\n"
        "wgmma.mma_async.sync.aligned.m64n128k16.f32.bf16.bf16 "
        "{%0,%1,%2,%3,%4,%5,%6,%7,%8,%9,%10,%11,%12,%13,%14,%15,%16,%17,%18,%19,%20,%21,%22,%23,%24,%25,%26,%27,%28,%29,%30,%31,%32,%33,%34,%35,%36,%37,%38,%39,%40,%41,%42,%43,%44,%45,%46,%47,%48,%49,%50,%51,%52,%53,%54,%55,%56,%57,%58,%59,%60,%61,%62,%63}, {%64,%65,%66,%67}, dsc, 1, 1, 1, 1;\n}\n"
        : "+f"(d[0]), "+f"(d[1]), "+f"(d[2]), "+f"(d[3]), "+f"(d[4]), "+f"(d[5]), "+f"(d[6]), "+f"(d[7]), "+f"(d[8]), "+f"(d[9]), "+f"(d[10]), "+f"(d[11]), "+f"(d[12]), "+f"(d[13]), "+f"(d[14]), "+f"(d[15]), "+f"(d[16]), "+f"(d[17]), "+f"(d[18]), "+f"(d[19]), "+f"(d[20]), "+f"(d[21]), "+f"(d[22]), "+f"(d[23]), "+f"(d[24]), "+f"(d[25]), "+f"(d[26]), "+f"(d[27]), "+f"(d[28]), "+f"(d[29]), "+f"(d[30]), "+f"(d[31]), "+f"(d[32]), "+f"(d[33]), "+f"(d[34]), "+f"(d[35]), "+f"(d[36]), "+f"(d[37]), "+f"(d[38]), "+f"(d[39]), "+f"(d[40]), "+f"(d[41]), "+f"(d[42]), "+f"(d[43]), "+f"(d[44]), "+f"(d[45]), "+f"(d[46]), "+f"(d[47]), "+f"(d[48]), "+f"(d[49]), "+f"(d[50]), "+f"(d[51]), "+f"(d[52]), "+f"(d[53]), "+f"(d[54]), "+f"(d[55]), "+f"(d[56]), "+f"(d[57]), "+f"(d[58]), "+f"(d[59]), "+f"(d[60]), "+f"(d[61]), "+f"(d[62]), "+f"(d[63])
        : "r"(a[0]), "r"(a[1]), "r"(a[2]), "r"(a[3]), "r"(dlo), "r"(dhi), "n"(OFF));
}
template <int OFF>
__device__ __forceinline__ void wgmma_rst_n64(float* d, const uint32_t* a, uint32_t dlo, uint32_t dhi) {
    asm volatile(
        "{\n.reg .b64 dsc;\n.reg .b32 lo;\nadd.s32 lo, %36, %38;\nmov.b64 dsc, {lo, %37};\n"
        "wgmma.mma_async.sync.aligned.m64n64k16.f32.bf16.bf16 "
        "{%0,%1,%2,%3,%4,%5,%6,%7,%8,%9,%10,%11,%12,%13,%14,%15,%16,%17,%18,%19,%20,%21,%22,%23,%24,%25,%26,%27,%28,%29,%30,%31}, {%32,%33,%34,%35}, dsc, 1, 1, 1, 1;\n}\n"
        : "+f"(d[0]), "+f"(d[1]), "+f"(d[2]), "+f"(d[3]), "+f"(d[4]), "+f"(d[5]), "+f"(d[6]), "+f"(d[7]), "+f"(d[8]), "+f"(d[9]), "+f"(d[10]), "+f"(d[11]), "+f"(d[12]), "+f"(d[13]), "+f"(d[14]), "+f"(d[15]), "+f"(d[16]), "+f"(d[17]), "+f"(d[18]), "+f"(d[19]), "+f"(d[20]), "+f"(d[21]), "+f"(d[22]), "+f"(d[23]), "+f"(d[24]), "+f"(d[25]), "+f"(d[26]), "+f"(d[27]), "+f"(d[28]), "+f"(d[29]), "+f"(d[30]), "+f"(d[31])
        : "r"(a[0]), "r"(a[1]), "r"(a[2]), "r"(a[3]), "r"(dlo), "r"(dhi), "n"(OFF));
}

constexpr int NSLOT = 14;
constexpr int SLOT = 16384;
constexpr int X_OFF = 10 * SLOT;
constexpr int BAR_OFF = NSLOT * SLOT;
constexpr int ONES_OFF = BAR_OFF + 512;
constexpr int SMEM_BYTES = BAR_OFF + 800 + 1024;
constexpr int PRE = 3;
constexpr int G1_LAG = 4;
constexpr int A_SLOT0 = 6;
constexpr int CV_BASE = PRE * SLOT;
constexpr int CV_R = 156;
constexpr int CV_XT_BYTES = 2 * CV_R * 16;
constexpr int CV_WT_BYTES = 2064 * 4;
constexpr int CV_P_BYTES = 3072 * 4;
constexpr int CV_CH_BYTES = CV_XT_BYTES + CV_WT_BYTES + 2 * CV_P_BYTES + 80;
static_assert(CV_CH_BYTES % 128 == 16, "channel pitch");
constexpr int CV_XS_OFF = CV_BASE + 4 * CV_CH_BYTES;
constexpr int CV_XS_PITCH = 4096 + 16;
constexpr int CV_ST_OFF = CV_XS_OFF + 4 * CV_XS_PITCH;
static_assert(CV_XS_OFF % 16 == 0 && CV_ST_OFF % 16 == 0 && CV_ST_OFF + 8192 <= BAR_OFF, "conv layout");
constexpr int cv_stage(int c) { return (CV_BASE + c * CV_CH_BYTES + CV_XT_BYTES + CV_WT_BYTES + 1023) / 1024 * 1024; }
constexpr int CV_KS_OFF = cv_stage(0), CV_VS_OFF = cv_stage(1), CV_XI_OFF = cv_stage(2);
static_assert(CV_KS_OFF + 1024 + 16384 <= CV_BASE + CV_CH_BYTES && CV_VS_OFF + 16384 <= CV_BASE + 2 * CV_CH_BYTES && CV_XI_OFF + 16384 <= CV_BASE + 3 * CV_CH_BYTES, "staging");

__device__ __forceinline__ void conv_load(uint32_t (&w)[6], const uint32_t* wp) {
#pragma unroll
    for (int s = 0; s < 2; s++) { w[3 * s] = wp[64 * s - 8]; w[3 * s + 1] = wp[64 * s]; w[3 * s + 2] = wp[64 * s + 8]; }
}
template <int L, int OFF>
__device__ __forceinline__ void conv_mma1(float* acc, uint32_t a2, uint32_t a0, uint32_t a1, uint32_t dlo, uint32_t dhi) {
    if (L == 0) wgmma_rs_n128<OFF>(acc, a0, a1, a2, a0, dlo, dhi);
    else if (L == 1) wgmma_rs_n128<OFF>(acc, a0, a1, a2, a0, dlo, dhi);
    else if (L == 2) wgmma_rs_n96<OFF>(acc, a0, a1, a2, a0, dlo, dhi);
    else if (L == 3) wgmma_rs_n96<OFF>(acc, a0, a1, a2, a0, dlo, dhi);
    else if (L == 4) wgmma_rs_n64<OFF>(acc, a0, a1, a2, a0, dlo, dhi);
    else if (L == 5) wgmma_rs_n64<OFF>(acc, a0, a1, a2, a0, dlo, dhi);
    else if (L == 6) wgmma_rs_n32<OFF>(acc, a0, a1, a2, a0, dlo, dhi);
    else wgmma_rs_n32<OFF>(acc, a0, a1, a2, a0, dlo, dhi);
}
template <int B>
__device__ __forceinline__ void conv_issue(float* acc, const uint32_t (&w)[6], uint32_t dlo, uint32_t dhi) {
    wgmma_fence();
    conv_mma1<(B >> 1), 8 * B + 0>(acc, w[0], w[1], w[2], dlo, dhi);
    conv_mma1<(B >> 1), 8 * B + 4>(acc, w[3], w[4], w[5], dlo, dhi);
    wgmma_commit();
}
template <int B>
__device__ __forceinline__ void conv_pair(float* acc, uint32_t (&q0)[6], uint32_t (&q1)[6], const uint32_t* wp, uint32_t dlo, uint32_t dhi) {
    if (B > 0 && (B & 3) == 0) wgmma_wait<0>();
    conv_issue<B>(acc, q0, dlo, dhi);
    if ((B & 3) != 0) wgmma_wait<1>();
    conv_load(q1, wp + 128 * (B + 1));
    conv_issue<B + 1>(acc, q1, dlo, dhi);
    if (B + 2 < 16) {
        wgmma_wait<1>();
        conv_load(q0, wp + 128 * (B + 2));
    }
}
__device__ __forceinline__ void conv_mma(float* acc, const uint32_t* wp, uint32_t xt_base) {
    uint32_t q0[6], q1[6];
    const uint64_t desc0 = make_desc(xt_base, CV_R * 16, 128, 0);
    const uint32_t dlo = (uint32_t)desc0, dhi = (uint32_t)(desc0 >> 32);
    conv_load(q0, wp);
    conv_pair<0>(acc, q0, q1, wp, dlo, dhi);
    conv_pair<2>(acc, q0, q1, wp, dlo, dhi);
    conv_pair<4>(acc, q0, q1, wp, dlo, dhi);
    conv_pair<6>(acc, q0, q1, wp, dlo, dhi);
    conv_pair<8>(acc, q0, q1, wp, dlo, dhi);
    conv_pair<10>(acc, q0, q1, wp, dlo, dhi);
    conv_pair<12>(acc, q0, q1, wp, dlo, dhi);
    conv_pair<14>(acc, q0, q1, wp, dlo, dhi);
    wgmma_wait<0>();
}
__device__ __forceinline__ float warp_sum(float v) {
#pragma unroll
    for (int o = 16; o > 0; o >>= 1) v += __shfl_xor_sync(0xffffffffu, v, o);
    return v;
}
__device__ __forceinline__ float sigmoid_f(float x) {
    float e, r;
    asm("ex2.approx.ftz.f32 %0, %1;" : "=f"(e) : "f"(x * -1.4426950408889634f));
    asm("rcp.approx.ftz.f32 %0, %1;" : "=f"(r) : "f"(1.f + e));
    return r;
}
__device__ __forceinline__ void st_async_v4(uint32_t addr, const uint32_t (&c)[4], uint32_t bar) {
    asm volatile("st.async.weak.shared::cluster.mbarrier::complete_tx::bytes.v4.b32 [%0], {%1,%2,%3,%4}, [%5];"
                 ::"r"(addr), "r"(c[0]), "r"(c[1]), "r"(c[2]), "r"(c[3]), "r"(bar) : "memory");
}

__device__ __forceinline__ void load_chunk_t(uint32_t addr_rows, int lane, uint32_t (&r)[4]) {
    asm volatile("ldmatrix.sync.aligned.m8n8.x4.trans.shared.b16 {%0,%1,%2,%3}, [%4];"
                 : "=r"(r[0]), "=r"(r[1]), "=r"(r[2]), "=r"(r[3]) : "r"(addr_rows + lane * 16) : "memory");
    const bool b0 = lane & 1, b1 = lane & 2;
    uint32_t x, y;
    x = b0 ? r[0] : r[1]; y = b0 ? r[2] : r[3];
    x = __shfl_xor_sync(0xffffffffu, x, 1); y = __shfl_xor_sync(0xffffffffu, y, 1);
    if (b0) { r[0] = x; r[2] = y; } else { r[1] = x; r[3] = y; }
    x = b1 ? r[0] : r[2]; y = b1 ? r[1] : r[3];
    x = __shfl_xor_sync(0xffffffffu, x, 2); y = __shfl_xor_sync(0xffffffffu, y, 2);
    if (b1) { r[0] = x; r[1] = y; } else { r[2] = x; r[3] = y; }
}

template <bool FULL>
__device__ __forceinline__ void gemm1_pass(int T, const uint32_t (&a)[32][4], float inv0, float inv1, uint32_t sb, uint32_t peer,
                                           int row0, int f0, int tid, int wg) {
    const int warp = tid >> 5, lane = tid & 31;
    const uint32_t barFull = sb + BAR_OFF, barEmpty = barFull + 8 * NSLOT;
    const uint64_t d0_ = FULL ? make_desc(sb, 8192, 1024, 1) : make_desc(sb, 4096, 512, 2);
    const uint32_t dlo0 = (uint32_t)d0_, dhi = (uint32_t)(d0_ >> 32);
    const uint32_t peerEmpty = mapa(barEmpty, peer);
    int st = (T * 8) % NSLOT, ph = ((T * 8) / NSLOT) & 1;
    constexpr int UO = FULL ? 32 : 16;
    float acc[2 * UO];
#pragma unroll
    for (int i = 0; i < 2 * UO; i++) acc[i] = 0.f;
#pragma unroll
    for (int kb = 0; kb < 8; kb++) {
        mbar_wait(barFull + 8 * st, ph);
        wgmma_fence();
        const uint32_t dlo = dlo0 + st * (SLOT / 16);
        if (FULL) {
            wgmma_rst_n128<0>(acc, a[4 * kb], dlo, dhi); wgmma_rst_n128<128>(acc, a[4 * kb + 1], dlo, dhi);
            wgmma_rst_n128<256>(acc, a[4 * kb + 2], dlo, dhi); wgmma_rst_n128<384>(acc, a[4 * kb + 3], dlo, dhi);
        } else {
            wgmma_rst_n64<0>(acc, a[4 * kb], dlo, dhi); wgmma_rst_n64<64>(acc, a[4 * kb + 1], dlo, dhi);
            wgmma_rst_n64<128>(acc, a[4 * kb + 2], dlo, dhi); wgmma_rst_n64<192>(acc, a[4 * kb + 3], dlo, dhi);
        }
        wgmma_commit();
        if (kb == G1_LAG) asm volatile("{\n.reg .pred p;\nsetp.eq.s32 p, %0, 0;\n@p bar.arrive 5, 256;\n}\n" ::"r"(wg + T) : "memory");
        if (kb > 0) {
            wgmma_wait<1>();
            if ((tid & 127) == 0) {
                const int pst = (st == 0) ? NSLOT - 1 : st - 1;
                mbar_arrive(barEmpty + 8 * pst);
                mbar_arrive_cluster(peerEmpty + 8 * pst);
            }
        }
        if (++st == NSLOT) { st = 0; ph ^= 1; }
    }
    wgmma_wait<0>();
    if ((tid & 127) == 0) {
        const int pst = (st == 0) ? NSLOT - 1 : st - 1;
        mbar_arrive(barEmpty + 8 * pst);
        mbar_arrive_cluster(peerEmpty + 8 * pst);
    }
    TS(1, 3 + 2 * T, tid == 0);
    TS(2, 12 + T, tid == 128);
    constexpr int NJ = FULL ? 8 : 4;
    uint32_t pk[NJ][2];
#pragma unroll
    for (int j = 0; j < NJ; j++) {
#pragma unroll
        for (int hf = 0; hf < 2; hf++) {
            const float inv = hf ? inv1 : inv0;
            const uint32_t gp = pack_bf16(acc[4 * j + 2 * hf] * inv, acc[4 * j + 2 * hf + 1] * inv);
            const uint32_t up = pack_bf16(acc[UO + 4 * j + 2 * hf] * inv, acc[UO + 4 * j + 2 * hf + 1] * inv);
            const uint32_t sp = pack_bf16(sigmoid_f(bf_lo(gp)), sigmoid_f(bf_hi(gp)));
            const bf162 pr = __hmul2_rn(*reinterpret_cast<const bf162*>(&sp), *reinterpret_cast<const bf162*>(&up));
            pk[j][hf] = *reinterpret_cast<const uint32_t*>(&pr);
        }
    }
    const int ns = f0;
    const int blk = 14 * (ns >> 2) + (FULL ? 4 * T + (ns & 3) : 12 + ((ns & 3) >> 1));
    uint4* dst = reinterpret_cast<uint4*>(g_hh) + ((size_t)(row0 >> 7) * 28 + blk) * 1024 + warp * 128 + (FULL ? 0 : (ns & 1) * 64) + lane;
#pragma unroll
    for (int j = 0; j < NJ; j += 2) dst[(j >> 1) * 32] = make_uint4(pk[j][0], pk[j][1], pk[j + 1][0], pk[j + 1][1]);
    asm volatile("bar.arrive %0, 160;" ::"r"(11 + wg) : "memory");
    TS(1, 4 + 2 * T, tid == 0);
}

constexpr int NA = 6;
__device__ __forceinline__ int g2_slotB(int j) { return 4 + (j & 7); }
__device__ __forceinline__ int g2_fillB(int j) { return 2 + (j >> 3); }
__device__ __forceinline__ int g2_slotA(int j) { return (12 + j % NA) % NSLOT; }
__device__ __forceinline__ int g2_fillA(int j) { return (j % NA < 2 ? 2 : 3) + j / NA; }

__global__ void __cluster_dims__(2, 1, 1) __launch_bounds__(512, 1)
mega_kernel(const bf16* __restrict__ xin, const bf16* __restrict__ kin, const bf16* __restrict__ vin, const bf16* __restrict__ shift_k,
            const bf16* __restrict__ ssm_k, const bf16* __restrict__ ssm_D,
            const bf16* __restrict__ w_gate, const bf16* __restrict__ w_up, const bf16* __restrict__ w_down, bf16* __restrict__ out,
            const __grid_constant__ CUtensorMap map_g, const __grid_constant__ CUtensorMap map_u,
            const __grid_constant__ CUtensorMap map_g32, const __grid_constant__ CUtensorMap map_u32,
            const __grid_constant__ CUtensorMap map_d, const __grid_constant__ CUtensorMap map_d32, const __grid_constant__ CUtensorMap map_k, const __grid_constant__ CUtensorMap map_kh,
            const __grid_constant__ CUtensorMap map_v, const __grid_constant__ CUtensorMap map_x) {
    extern __shared__ uint8_t smem_raw[];
    uint8_t* smem = smem_raw + ((1024u - (smem_u32(smem_raw) & 1023u)) & 1023u);
    const uint32_t sb = smem_u32(smem);
    const uint32_t barFull = sb + BAR_OFF, barEmpty = barFull + 8 * NSLOT, barA = barEmpty + 8 * NSLOT;
    const uint32_t barKV = barA + 64, barXS = barKV + 8, barX = barXS + 8, barKin = barX + 8, barXin = barKin + 8, barAE = barXin + 8, barG1 = barAE + 48, barRdy = barG1 + 8, barKi = barRdy + 8;
    const int tid = threadIdx.x, warp = tid >> 5, lane = tid & 31;
    const int bid = blockIdx.x;
    const int rank = bid & 1;
    const int d0 = bid * 4, dp = (bid >> 1) * 8;
    const int ns = (bid >> 1) & 7, mt1 = 2 * (bid >> 4) + rank;
    const int f0 = ns * 224;
    const int mt2 = bid >> 3, nt = (bid >> 1) & 3;
    TS_INIT();
    TS(0, 0, tid == 0);

    if (tid == 0) {
        for (int i = 0; i < NSLOT; i++) { mbar_init(barFull + 8 * i, 1); mbar_init(barEmpty + 8 * i, 4); }
        for (int i = 0; i < 8; i++) mbar_init(barA + 8 * i, 1);
        mbar_init(barKV, 1);
        mbar_init(barXS, 2);
        mbar_init(barX, 1);
        for (int i = 0; i < NA; i++) mbar_init(barAE + 8 * i, 8);
        mbar_init(barRdy, 2);
        *reinterpret_cast<volatile unsigned int*>(smem + ONES_OFF + 256) = 0u;
        mbar_init(barG1, 1);
        for (int i = 0; i < 4; i++) mbar_init(barKi + 8 * i, 1);
        mbar_init(barKin, 1);
        mbar_init(barXin, 1);
        asm volatile("fence.mbarrier_init.release.cluster;" ::: "memory");
        mbar_expect_tx(barKV, 16384);
        mbar_expect_tx(barXS, 16384);
        mbar_expect_tx(barX, 32768);
        for (int i = 0; i < 4; i++) {
            mbar_expect_tx(barKi + 8 * i, i == 0 ? 8192 + 128 : 8192);
            if (i == 0) tma_load_2d(sb + CV_KS_OFF + 896, &map_kh, barKi, dp, 1024 * rank - 8);
            tma_load_2d(sb + CV_KS_OFF + 1024 + i * 4096, &map_k, barKi + 8 * i, dp, 1024 * rank + 256 * i);
            tma_load_2d(sb + CV_VS_OFF + i * 4096, &map_v, barKi + 8 * i, dp, 1024 * rank + 256 * i);
        }
        mbar_expect_tx(barXin, 16384);
        for (int i = 0; i < 4; i++) tma_load_2d(sb + CV_XI_OFF + i * 4096, &map_x, barXin, dp, 1024 * rank + 256 * i);
    }
    __syncwarp();
    asm volatile("barrier.cluster.arrive.relaxed.aligned;" ::: "memory");
    const uint2 dD = __ldg(reinterpret_cast<const uint2*>(ssm_D + d0));

    if (tid < 256) {
        uint32_t w[4][4];
#pragma unroll
        for (int cp = 0; cp < 4; cp++) {
            const uint4 sw = __ldg(reinterpret_cast<const uint4*>(shift_k + (dp + 2 * cp) * 4));
            w[0][cp] = __byte_perm(sw.x, sw.z, 0x5410); w[1][cp] = __byte_perm(sw.x, sw.z, 0x7632);
            w[2][cp] = __byte_perm(sw.y, sw.w, 0x5410); w[3][cp] = __byte_perm(sw.y, sw.w, 0x7632);
        }
        asm volatile("bar.sync 1, 512;" ::: "memory");
        cluster_wait();
        const int g = lane >> 2, t = lane & 3;
        const uint32_t dbase = mapa(sb, g >> 2);
#pragma unroll 1
        for (int i = 0; i < 4; i++) {
            mbar_wait(barKi + 8 * i, 0);
            const int row = tid + 256 * i;
            const uint4* ks = reinterpret_cast<const uint4*>(smem + CV_KS_OFF + 1024) + row;
            uint4* vs = reinterpret_cast<uint4*>(smem + CV_VS_OFF) + row;
            const uint4 k0 = ks[-3], k1 = ks[-2], k2 = ks[-1], k3 = ks[0], vv = vs[0];
            const uint32_t ka[4][4] = {{k0.x, k0.y, k0.z, k0.w}, {k1.x, k1.y, k1.z, k1.w}, {k2.x, k2.y, k2.z, k2.w}, {k3.x, k3.y, k3.z, k3.w}};
            const uint32_t va[4] = {vv.x, vv.y, vv.z, vv.w};
            uint32_t o[4];
#pragma unroll
            for (int cp = 0; cp < 4; cp++) {
                bf162 acc2 = __hmul2_rn(*reinterpret_cast<const bf162*>(&ka[0][cp]), *reinterpret_cast<const bf162*>(&w[3][cp]));
#pragma unroll
                for (int t = 1; t < 4; t++)
                    acc2 = __hadd2_rn(acc2, __hmul2_rn(*reinterpret_cast<const bf162*>(&ka[t][cp]), *reinterpret_cast<const bf162*>(&w[3 - t][cp])));
                acc2 = __hmul2_rn(acc2, *reinterpret_cast<const bf162*>(&va[cp]));
                o[cp] = *reinterpret_cast<uint32_t*>(&acc2);
            }
            vs[0] = make_uint4(o[0], o[1], o[2], o[3]);
            __syncwarp();
            const int row0 = 32 * warp + 256 * i;
            uint32_t c[4];
            load_chunk_t(sb + CV_VS_OFF + row0 * 16, lane, c);
            const int p = 128 * rank + (row0 >> 3) + t;
            st_async_v4(dbase + CV_BASE + (g & 3) * CV_CH_BYTES + ((p & 1) * CV_R + 127 - (p >> 1)) * 16, c, dbase + BAR_OFF + (barKV - barFull));
        }
    } else {
        const int u = tid - 256;
        const int lrow = bid * 16 + 2 * (u >> 5);
        const uint4* xp = reinterpret_cast<const uint4*>(xin + (size_t)lrow * D_ + lane * 16);
        uint4 xa[2], xb[2];
        xa[0] = __ldg(xp); xb[0] = __ldg(xp + 1); xa[1] = __ldg(xp + 64); xb[1] = __ldg(xp + 65);
        uint4 kk[4]; uint32_t prev[4];
#pragma unroll
        for (int c = 0; c < 4; c++) {
            const bf16* kp = ssm_k + (size_t)(d0 + c) * S_ + 8 * u;
            kk[c] = __ldg(reinterpret_cast<const uint4*>(kp));
            prev[c] = (u > 0) ? (uint32_t)__ldg(reinterpret_cast<const unsigned short*>(kp - 1)) : 0u;
        }
        asm volatile("bar.sync 1, 512;" ::: "memory");
        if (u < 224) *reinterpret_cast<uint4*>(smem + CV_BASE + (u / 56) * CV_CH_BYTES + (((u % 56) / 28) * CV_R + 128 + (u % 28)) * 16) = make_uint4(0, 0, 0, 0);
        if (u < 64) reinterpret_cast<uint32_t*>(smem + CV_BASE + (u >> 4) * CV_CH_BYTES + CV_XT_BYTES)[u & 15] = 0;
        else if (u < 128) reinterpret_cast<uint32_t*>(smem + ONES_OFF)[u - 64] = 0x3F803F80u;
#pragma unroll
        for (int c = 0; c < 4; c++) {
            uint4 lo, hi;
            lo.x = (kk[c].x & 0xffffu) | (prev[c] << 16);
            lo.y = __byte_perm(kk[c].x, 0, 0x1032);
            lo.z = __byte_perm(kk[c].y, kk[c].x, 0x7610);
            lo.w = __byte_perm(kk[c].y, 0, 0x1032);
            hi.x = __byte_perm(kk[c].z, kk[c].y, 0x7610);
            hi.y = __byte_perm(kk[c].z, 0, 0x1032);
            hi.z = __byte_perm(kk[c].w, kk[c].z, 0x7610);
            hi.w = __byte_perm(kk[c].w, 0, 0x1032);
            uint4* dst = reinterpret_cast<uint4*>(smem + CV_BASE + c * CV_CH_BYTES + CV_XT_BYTES + (16 + 8 * u) * 4);
            dst[0] = lo; dst[1] = hi;
        }
        fence_proxy_async();
        __syncwarp();
        asm volatile("bar.arrive 2, 512;" ::: "memory");
        asm volatile("bar.sync 3, 256;" ::: "memory");
#pragma unroll
        for (int r = 0; r < 2; r++) {
            const uint32_t xw[8] = {xa[r].x, xa[r].y, xa[r].z, xa[r].w, xb[r].x, xb[r].y, xb[r].z, xb[r].w};
            float sm_ = 0.f;
#pragma unroll
            for (int i = 0; i < 8; i++) sm_ += bf_lo(xw[i]) + bf_hi(xw[i]);
            sm_ = warp_sum(sm_);
            const float mean = sm_ * (1.f / 512.f);
            float q = 0.f;
#pragma unroll
            for (int i = 0; i < 8; i++) { float d1 = bf_lo(xw[i]) - mean, d2 = bf_hi(xw[i]) - mean; q += d1 * d1 + d2 * d2; }
            q = warp_sum(q);
            if (lane == 0) {
                g_stats[lrow + r] = pack_bf16(mean, sqrtf(bf16r(bf16r(q * (1.f / 512.f)) + 1e-5f)));
            }
        }
        if (lane == 0) {
            __threadfence();
            const unsigned int old = atomicAdd(&g_bar, 1u);
            if (u == 0) *reinterpret_cast<volatile unsigned int*>(smem + ONES_OFF + 256) = (old / 1024u + 1u) * 1024u + 1u;
        }
        __syncwarp();
        cluster_wait();
        if (u == 32) {
            const CUtensorMap* mw = rank ? &map_u : &map_g;
            for (int it = 0; it < PRE; it++) {
                mbar_expect_tx(barFull + 8 * it, SLOT);
                tma_load_2d_mc(sb + it * SLOT + rank * 8192, mw, barFull + 8 * it, f0, 64 * it, (uint16_t)3);
            }
        }
    }
    TS(0, 1, tid == 0);
    mbar_wait(barKV, 0);
    fence_proxy_async();
    if (tid < 256) asm volatile("bar.sync 2, 512;" ::: "memory");

    const int wg = __shfl_sync(0xffffffffu, tid >> 7, 0);
    {
        const int wq = warp & 3, g = lane >> 2, t = lane & 3;
        uint8_t* chs = smem + CV_BASE + wg * CV_CH_BYTES;
        float acc[64];
#pragma unroll
        for (int i = 0; i < 64; i++) acc[i] = 0.f;
        const uint32_t* wp = reinterpret_cast<const uint32_t*>(chs + CV_XT_BYTES) + 16 + 16 * wq + g - 2 * t;
        conv_mma(acc, wp, smem_u32(chs));
        TS(0, 4 + wg, (tid & 127) == 0);
        if (wg < 2) {
            if (tid == 0) {
                unsigned int v;
                asm volatile("ld.acquire.gpu.global.u32 %0, [%1];" : "=r"(v) : "l"(&g_bar) : "memory");
                unsigned int target = 0;
                for (unsigned int it = 0; target == 0u && it < (1u << 22); it++) target = *reinterpret_cast<volatile unsigned int*>(smem + ONES_OFF + 256);
                target -= 1u;
                for (unsigned int it = 0; (int)(v - target) < 0 && it < (1u << 22); it++) asm volatile("ld.acquire.gpu.global.u32 %0, [%1];" : "=r"(v) : "l"(&g_bar) : "memory");
                fence_proxy_async_global();
                mbar_expect_tx(barXS, 8192);
                asm volatile("cp.async.bulk.shared::cluster.global.mbarrier::complete_tx::bytes [%0], [%1], %2, [%3];"
                             ::"r"(sb + CV_ST_OFF), "l"(g_stats), "r"(8192), "r"(barXS) : "memory");
                constexpr int SH = D_ * F_ * 2 / 128;
                asm volatile("cp.async.bulk.prefetch.L2.global [%0], %1;" ::"l"(reinterpret_cast<const uint8_t*>(w_gate) + (size_t)bid * SH), "r"(SH) : "memory");
                asm volatile("cp.async.bulk.prefetch.L2.global [%0], %1;" ::"l"(reinterpret_cast<const uint8_t*>(w_up) + (size_t)bid * SH), "r"(SH) : "memory");
                asm volatile("cp.async.bulk.prefetch.L2.global [%0], %1;" ::"l"(reinterpret_cast<const uint8_t*>(w_down) + (size_t)bid * SH), "r"(SH) : "memory");
            }
            __syncwarp();
        }
        {
            const uint32_t dbase = mapa(sb, g >> 2);
            mbar_wait(barXin, 0);
#pragma unroll 1
            for (int i = 0; i < 2; i++) {
                const int row0 = 32 * warp + 512 * i;
                uint32_t c[4];
                load_chunk_t(sb + CV_XI_OFF + row0 * 16, lane, c);
                const int p = 128 * rank + (row0 >> 3) + t;
                st_async_v4(dbase + CV_XS_OFF + (g & 3) * CV_XS_PITCH + p * 16, c, dbase + BAR_OFF + (barXS - barFull));
            }
            if (wg == 2) asm volatile("bar.sync 10, 512;" ::: "memory");
            else asm volatile("bar.arrive 10, 512;" ::: "memory");
        }
        const uint32_t pbase = smem_u32(chs + CV_XT_BYTES + CV_WT_BYTES + (wq & 1) * CV_P_BYTES);
        uint32_t pa[4];
        bool ok0[4];
#pragma unroll
        for (int e = 0; e < 4; e++) {
            const int s = 16 * (127 - 2 * t) + 16 * wq + g - 16 * (e & 1) + 8 * (e >> 1);
            pa[e] = pbase + (s + 4 * (s >> 3)) * 4;
            ok0[e] = s < S_;
        }
        if (wq < 2) {
#pragma unroll
            for (int i = 0; i < 64; i++) {
                const int e = (i & 1) | (i & 2);
                if (i >= 4 || ok0[e]) asm volatile("st.shared.f32 [%0], %1;" ::"r"(pa[e] - 768 * (i >> 2)), "f"(acc[i]) : "memory");
            }
            if (wq == 1 && lane < 16) asm volatile("st.shared.f32 [%0], %1;" ::"r"(pbase + (lane + 4 * (lane >> 3)) * 4), "f"(0.f) : "memory");
        }
        asm volatile("bar.sync %0, 128;" ::"r"(6 + wg) : "memory");
        if (wq >= 2) {
#pragma unroll
            for (int i0 = 0; i0 < 64; i0 += 16) {
                float o[16];
#pragma unroll
                for (int i = i0; i < i0 + 16; i++) {
                    const int e = (i & 1) | (i & 2);
                    o[i - i0] = 0.f;
                    if (i >= 4 || ok0[e]) asm volatile("ld.shared.f32 %0, [%1];" : "=f"(o[i - i0]) : "r"(pa[e] - 768 * (i >> 2)));
                }
#pragma unroll
                for (int i = i0; i < i0 + 16; i++) {
                    const int e = (i & 1) | (i & 2);
                    if (i >= 4 || ok0[e]) asm volatile("st.shared.f32 [%0], %1;" ::"r"(pa[e] - 768 * (i >> 2)), "f"(o[i - i0] + acc[i]) : "memory");
                }
            }
        }
    }
    TS(0, 10, tid == 0);
    TS(0, 11, tid == 480);
    mbar_wait(barXS, 0);
    asm volatile("bar.sync %0, 128;" ::"r"(6 + wg) : "memory");
    TS(0, 8, tid == 0);
    {
        const int c = wg, lt = tid & 127;
        const uint8_t* cb = smem + CV_BASE + c * CV_CH_BYTES;
        const uint32_t dw = (c & 2) ? dD.y : dD.x;
        const float Dv = (c & 1) ? bf_hi(dw) : bf_lo(dw);
#pragma unroll 1
        for (int it = 0; it < 2; it++) {
            const int p = lt + 128 * it;
            const int s0 = 8 * p;
            const float4* p0 = reinterpret_cast<const float4*>(cb + CV_XT_BYTES + CV_WT_BYTES + p * 48);
            const float4* p1 = reinterpret_cast<const float4*>(cb + CV_XT_BYTES + CV_WT_BYTES + CV_P_BYTES + p * 48);
            const uint4 kv = *reinterpret_cast<const uint4*>(cb + ((p & 1) * CV_R + 127 - (p >> 1)) * 16);
            const uint4 xv = *reinterpret_cast<const uint4*>(smem + CV_XS_OFF + c * CV_XS_PITCH + p * 16);
            const uint4 sa_ = *reinterpret_cast<const uint4*>(smem + CV_ST_OFF + s0 * 4), sb_ = *reinterpret_cast<const uint4*>(smem + CV_ST_OFF + s0 * 4 + 16);
            const uint32_t sw_[8] = {sa_.x, sa_.y, sa_.z, sa_.w, sb_.x, sb_.y, sb_.z, sb_.w};
            const float4 a0 = p0[0], a1 = p0[1], b0 = p1[0], b1 = p1[1];
            float y[8] = {a0.x + b0.x, a0.y + b0.y, a0.z + b0.z, a0.w + b0.w, a1.x + b1.x, a1.y + b1.y, a1.z + b1.z, a1.w + b1.w};
            const uint32_t kw[4] = {kv.x, kv.y, kv.z, kv.w};
            const uint32_t xw[4] = {xv.x, xv.y, xv.z, xv.w};
            uint32_t ow[4];
#pragma unroll
            for (int j = 0; j < 4; j++) {
                float e0 = bf_lo(kw[j]) * Dv, e1 = bf_hi(kw[j]) * Dv;
                bf16r2(e0, e1);
                bf16r2(y[2 * j], y[2 * j + 1]);
                const uint32_t zp = pack_bf16(y[2 * j] + e0, y[2 * j + 1] + e1);
                float q0 = bf_lo(xw[j]) - bf_lo(sw_[2 * j]), q1 = bf_hi(xw[j]) - bf_lo(sw_[2 * j + 1]);
                bf16r2(q0, q1);
                const uint32_t qp = pack_bf16(__fdividef(q0, bf_hi(sw_[2 * j])), __fdividef(q1, bf_hi(sw_[2 * j + 1])));
                const bf162 qz = __hmul2_rn(*reinterpret_cast<const bf162*>(&qp), *reinterpret_cast<const bf162*>(&zp));
                const bf162 hv = __hadd2_rn(*reinterpret_cast<const bf162*>(&xw[j]), qz);
                ow[j] = *reinterpret_cast<const uint32_t*>(&hv);
            }
            TS(0, 13, tid == 0 && it == 0);
            asm volatile("st.global.v4.u32 [%0], {%1,%2,%3,%4};" ::"l"(g_hb + (size_t)(p >> 1) * (D_ * 16) + (d0 + c) * 16 + ((p & 1) ^ rank) * 8),
                         "r"(ow[0]), "r"(ow[1]), "r"(ow[2]), "r"(ow[3]) : "memory");
            TS(0, 14, tid == 0 && it == 0);
        }
    }
    TS(0, 12, tid == 0);
    asm volatile("bar.sync %0, 128;" ::"r"(6 + wg) : "memory");
    if ((tid & 127) == 96) {
        __threadfence();
        atomicAdd(&g_c1, 1u);
    }
    fence_proxy_async();
    __syncthreads();
    TS(0, 9, tid == 0);

    if (wg >= 2) {
        asm volatile("setmaxnreg.dec.sync.aligned.u32 24;");
        if (warp == 12 || warp == 13) {
            for (int T = 0; T < 4; T++) {
                asm volatile("bar.sync %0, 160;" ::"r"(warp - 1) : "memory");
                if (lane == 0) {
                    __threadfence();
                    atomicAdd(&g_c2[(mt1 * 2 + (ns >> 2)) * 4 + T], 1u);
                }
                __syncwarp();
            }
        }
        if (tid == 256) {
            for (int i = 0; i < 3; i++) {
                const uint32_t e = barEmpty + 8 * (PRE + i);
                asm volatile("mbarrier.arrive.shared::cta.b64 _, [%0], 2;" ::"r"(e) : "memory");
                asm volatile("mbarrier.arrive.shared::cluster.b64 _, [%0], 2;" ::"r"(mapa(e, rank ^ 1)) : "memory");
            }
            wait_counter(&g_c1, 512u);
            fence_proxy_async_global();
            TS(1, 11, true);
            for (int i = 0; i < 8; i++) {
                mbar_expect_tx(barA + 8 * i, 16384);
                asm volatile("cp.async.bulk.shared::cluster.global.mbarrier::complete_tx::bytes [%0], [%1], %2, [%3];"
                             ::"r"(sb + (A_SLOT0 + i) * SLOT), "l"(g_hb + (size_t)(mt1 * 8 + i) * (D_ * 16)), "r"(16384), "r"(barA + 8 * i) : "memory");
            }
            for (int T = 0; T < 2; T++) wait_counter(&g_c2[(2 * mt2 + rank) * 4 + T], 8u);
            fence_proxy_async_global();
            mbar_wait(barG1, 0);
            for (int j = 0; j < 14; j++) {
                const int st = g2_slotA(j), f = g2_fillA(j);
                if (j == 8 || j == 12) {
                    wait_counter(&g_c2[(2 * mt2 + rank) * 4 + (j >> 2)], 8u);
                    fence_proxy_async_global();
                }
                if (j < NA) mbar_wait(barEmpty + 8 * st, (f - (st < PRE ? 1 : 0)) & 1);
                else mbar_wait(barAE + 8 * (j % NA), (j / NA - 1) & 1);
                mbar_expect_tx(barFull + 8 * st, SLOT);
                asm volatile("cp.async.bulk.shared::cluster.global.mbarrier::complete_tx::bytes [%0], [%1], %2, [%3];"
                             ::"r"(sb + st * SLOT), "l"(reinterpret_cast<const uint8_t*>(g_hh) + ((size_t)mt2 * 28 + rank * 14 + j) * 16384), "r"(16384), "r"(barFull + 8 * st) : "memory");
            }
        } else if (tid == 288) {
            const CUtensorMap* mw = rank ? &map_u : &map_g;
            for (int it = PRE; it < 32; it++) {
                const int st = it % NSLOT, f = it / NSLOT;
                mbar_wait(barEmpty + 8 * st, (f - (st < PRE ? 1 : 0)) & 1);
                if (it < 24) {
                    mbar_expect_tx(barFull + 8 * st, SLOT);
                    tma_load_2d_mc(sb + st * SLOT + rank * 8192, mw, barFull + 8 * st, f0 + 64 * (it >> 3), 64 * (it & 7), (uint16_t)3);
                } else {
                    mbar_expect_tx(barFull + 8 * st, SLOT / 2);
                    tma_load_2d_mc(sb + st * SLOT + rank * 4096, rank ? &map_u32 : &map_g32, barFull + 8 * st, f0 + 192, 64 * (it & 7), (uint16_t)3);
                }
            }
            mbar_arrive(barG1);
            const int c0 = nt * 128, k0 = rank * 896;
            for (int j = 0; j < 14; j++) {
                const int st = g2_slotB(j), f = g2_fillB(j);
                mbar_wait(barEmpty + 8 * st, (f - (st < PRE ? 1 : 0)) & 1);
                mbar_expect_tx(barFull + 8 * st, SLOT);
                if (j < 12) {
                    const int kr = k0 + 224 * (j & 3) + 64 * (j >> 2);
                    tma_load_2d(sb + st * SLOT, &map_d, barFull + 8 * st, c0, kr);
                    tma_load_2d(sb + st * SLOT + 8192, &map_d, barFull + 8 * st, c0 + 64, kr);
                } else {
                    const int kr = k0 + 448 * (j - 12) + 192;
                    tma_load_2d(sb + st * SLOT, &map_d32, barFull + 8 * st, c0, kr);
                    tma_load_2d(sb + st * SLOT + 4096, &map_d32, barFull + 8 * st, c0, kr + 224);
                    tma_load_2d(sb + st * SLOT + 8192, &map_d32, barFull + 8 * st, c0 + 64, kr);
                    tma_load_2d(sb + st * SLOT + 12288, &map_d32, barFull + 8 * st, c0 + 64, kr + 224);
                }
            }
        }
    } else {
        asm volatile("setmaxnreg.inc.sync.aligned.u32 232;");
        const int row1 = mt1 * 128;
        {
            uint32_t a[32][4];
            {
                const uint32_t abase = sb + (A_SLOT0 + warp) * SLOT + ((lane & 7) + 8 * (lane >> 4)) * 32 + (((lane >> 3) ^ (lane >> 2)) & 1) * 16;
                mbar_wait(barA + 8 * warp, 0);
                TS(1, 12, tid == 0);
#pragma unroll
                for (int kk = 0; kk < 32; kk++) {
                    asm volatile("ldmatrix.sync.aligned.m8n8.x4.trans.shared.b16 {%0,%1,%2,%3}, [%4];"
                                 : "=r"(a[kk][0]), "=r"(a[kk][1]), "=r"(a[kk][2]), "=r"(a[kk][3])
                                 : "r"(abase + kk * 512) : "memory");
                }
            }
            TS(1, 14, tid == 0);
            float inv0, inv1;
            {
                float rs[4] = {0.f, 0.f, 0.f, 0.f};
                const uint64_t dones = make_desc(sb + ONES_OFF, 128, 128, 0);
                wgmma_fence();
#pragma unroll
                for (int kk = 0; kk < 32; kk++) wgmma_rs_n8<0>(rs, a[kk][0], a[kk][1], a[kk][2], a[kk][3], (uint32_t)dones, (uint32_t)(dones >> 32));
                wgmma_commit();
                float ga = 0.f, gb = 0.f, gc = 0.f, gd = 0.f;
#pragma unroll
                for (int kk = 0; kk < 32; kk++) {
                    float l, h;
                    l = bf_lo(a[kk][0]); h = bf_hi(a[kk][0]); ga += l * l; gc += h * h;
                    l = bf_lo(a[kk][2]); h = bf_hi(a[kk][2]); ga += l * l; gc += h * h;
                    l = bf_lo(a[kk][1]); h = bf_hi(a[kk][1]); gb += l * l; gd += h * h;
                    l = bf_lo(a[kk][3]); h = bf_hi(a[kk][3]); gb += l * l; gd += h * h;
                }
                ga += gc; gb += gd;
                ga += __shfl_xor_sync(0xffffffffu, ga, 1); ga += __shfl_xor_sync(0xffffffffu, ga, 2);
                gb += __shfl_xor_sync(0xffffffffu, gb, 1); gb += __shfl_xor_sync(0xffffffffu, gb, 2);
                wgmma_wait<0>();
                if (lane == 0) {
                    const uint32_t e = barEmpty + 8 * (A_SLOT0 + warp);
                    asm volatile("mbarrier.arrive.shared::cta.b64 _, [%0], 2;" ::"r"(e) : "memory");
                    asm volatile("mbarrier.arrive.shared::cluster.b64 _, [%0], 2;" ::"r"(mapa(e, rank ^ 1)) : "memory");
                }
                const float mean0 = rs[0] * (1.f / 512.f), mean1 = rs[2] * (1.f / 512.f);
                const uint32_t mp = pack_bf16(mean0, mean1);
                const uint32_t m0 = __byte_perm(mp, 0, 0x1010), m1 = __byte_perm(mp, 0, 0x3232);
#pragma unroll
                for (int kk = 0; kk < 32; kk++) {
#pragma unroll
                    for (int r = 0; r < 4; r++) {
                        const uint32_t mm = (r & 1) ? m1 : m0;
                        const bf162 dd = __hsub2_rn(*reinterpret_cast<const bf162*>(&a[kk][r]), *reinterpret_cast<const bf162*>(&mm));
                        a[kk][r] = *reinterpret_cast<const uint32_t*>(&dd);
                    }
                }
                const float v0 = fmaxf(ga * (1.f / 512.f) - mean0 * mean0, 0.f), v1 = fmaxf(gb * (1.f / 512.f) - mean1 * mean1, 0.f);
                inv0 = __fdividef(1.f, bf16r(sqrtf(bf16r(bf16r(v0) + 1e-5f))));
                inv1 = __fdividef(1.f, bf16r(sqrtf(bf16r(bf16r(v1) + 1e-5f))));
            }
            TS(1, 2, tid == 0);
            if (wg == 1) asm volatile("bar.sync 5, 256;" ::: "memory");
#pragma unroll 1
            for (int T = 0; T < 3; T++) gemm1_pass<true>(T, a, inv0, inv1, sb, rank ^ 1, row1, ns, tid, wg);
            gemm1_pass<false>(3, a, inv0, inv1, sb, rank ^ 1, row1, ns, tid, wg);
        }
        TS(2, 0, tid == 0);

        {
        uint32_t sb_, tid_;
        asm volatile("mov.u32 %0, %1;" : "=r"(sb_) : "r"(sb) : "memory");
        asm volatile("mov.u32 %0, %%tid.x;" : "=r"(tid_) :: "memory");
        const uint32_t sb = sb_;
        const int tid = (int)tid_, warp = tid >> 5, lane = tid & 31;
        const uint32_t barFull = sb + BAR_OFF, barEmpty = barFull + 8 * NSLOT, barA = barEmpty + 8 * NSLOT;
        const uint32_t barX = barA + 64 + 16, barAE = barX + 24, barRdy = barAE + 56;
        const int c0 = nt * 128, row2 = mt2 * 128;
        float acc[64];
#pragma unroll
        for (int i = 0; i < 64; i++) acc[i] = 0.f;
        {
            uint32_t a[2][4][4];
            const uint64_t d0_ = make_desc(sb, 8192, 1024, 1);
            const uint32_t dlo0 = (uint32_t)d0_, dhi = (uint32_t)(d0_ >> 32);
            const uint32_t abase = sb + warp * 2048 + lane * 16;
#pragma unroll
            for (int j = 0; j < 14; j++) {
                const int jj = j & 1;
                const int sa = g2_slotA(j), sbk = g2_slotB(j);
                mbar_wait(barFull + 8 * sa, g2_fillA(j) & 1);
                if (j >= 2) {
                    wgmma_wait<1>();
                    if (j < 8 && (tid & 127) == 0) asm volatile("mbarrier.arrive.shared::cta.b64 _, [%0], 2;" ::"r"(barEmpty + 8 * g2_slotB(j - 2)) : "memory");
                    if (j == 9 && (tid & 127) == 0) mbar_arrive_cluster(mapa(barRdy, rank ^ 1));
                }
#pragma unroll
                for (int kk = 0; kk < 4; kk++)
                    asm volatile("ld.shared.v4.u32 {%0,%1,%2,%3}, [%4];" : "=r"(a[jj][kk][0]), "=r"(a[jj][kk][1]), "=r"(a[jj][kk][2]), "=r"(a[jj][kk][3])
                                 : "r"(abase + sa * SLOT + kk * 512) : "memory");
                mbar_wait(barFull + 8 * sbk, g2_fillB(j) & 1);
                if ((j & 1) == 0) TS(2, 5 + (j >> 1), tid == 128);
                wgmma_fence();
                const uint32_t dlo = dlo0 + sbk * (SLOT / 16);
                wgmma_rst_n128<0>(acc, a[jj][0], dlo, dhi); wgmma_rst_n128<128>(acc, a[jj][1], dlo, dhi);
                wgmma_rst_n128<256>(acc, a[jj][2], dlo, dhi); wgmma_rst_n128<384>(acc, a[jj][3], dlo, dhi);
                wgmma_commit();
                if (j < 14 - NA) {
                    __syncwarp();
                    if (lane == 0) asm volatile("mbarrier.arrive.shared::cta.b64 _, [%0];" ::"r"(barAE + 8 * (j % NA)) : "memory");
                }
            }
        }
        uint4 hv[4];
        {
            const uint4* hsrc = reinterpret_cast<const uint4*>(g_hb + (size_t)(mt2 * 8 + warp) * (D_ * 16) + (c0 + 64 * rank) * 16);
#pragma unroll
            for (int i = 0; i < 4; i++) hv[i] = __ldcg(hsrc + lane + 32 * i);
        }
        wgmma_wait<0>();
        TS(2, 1 + wg, (tid & 127) == 0);
        {
            const uint32_t dst = mapa(sb + X_OFF + tid * 16, rank ^ 1);
            const uint32_t dbar = mapa(barX, rank ^ 1);
            mbar_wait(barRdy, 0);
#pragma unroll
            for (int j = 0; j < 8; j++) {
                uint32_t v[4];
#pragma unroll
                for (int e = 0; e < 4; e++) v[e] = __float_as_uint(rank == 0 ? acc[32 + 4 * j + e] : acc[4 * j + e]);
                st_async_v4(dst + j * 4096, v, dbar);
            }
        }
        asm volatile("bar.sync 4, 256;" ::: "memory");
        const uint32_t stg = sb + warp * 2048;
#pragma unroll
        for (int i = 0; i < 4; i++)
            asm volatile("st.shared.v4.u32 [%0], {%1,%2,%3,%4};" ::"r"(stg + (lane + 32 * i) * 16), "r"(hv[i].x), "r"(hv[i].y), "r"(hv[i].z), "r"(hv[i].w) : "memory");
        __syncwarp();
        uint32_t hf_[8][2];
#pragma unroll
        for (int j = 0; j < 8; j += 2) {
            asm volatile("ldmatrix.sync.aligned.m8n8.x4.trans.shared.b16 {%0,%1,%2,%3}, [%4];"
                         : "=r"(hf_[j][0]), "=r"(hf_[j][1]), "=r"(hf_[j + 1][0]), "=r"(hf_[j + 1][1])
                         : "r"(stg + (8 * j + (lane & 7) + 8 * (lane >> 4)) * 32 + (((lane >> 3) ^ (lane >> 2)) & 1) * 16) : "memory");
        }
        __syncwarp();
        mbar_wait(barX, 0);
        uint32_t po[8][2];
#pragma unroll
        for (int j = 0; j < 8; j++) {
            float4 v;
            asm volatile("ld.shared.v4.f32 {%0,%1,%2,%3}, [%4];" : "=f"(v.x), "=f"(v.y), "=f"(v.z), "=f"(v.w) : "r"(sb + X_OFF + tid * 16 + j * 4096));
            float o0, o1, o2, o3;
            if (rank == 0) { o0 = acc[4 * j] + v.x; o1 = acc[4 * j + 1] + v.y; o2 = acc[4 * j + 2] + v.z; o3 = acc[4 * j + 3] + v.w; }
            else { o0 = acc[32 + 4 * j] + v.x; o1 = acc[33 + 4 * j] + v.y; o2 = acc[34 + 4 * j] + v.z; o3 = acc[35 + 4 * j] + v.w; }
            bf16r2(o0, o1); bf16r2(o2, o3);
            po[j][0] = pack_bf16(bf_lo(hf_[j][0]) + o0, bf_hi(hf_[j][0]) + o1);
            po[j][1] = pack_bf16(bf_lo(hf_[j][1]) + o2, bf_hi(hf_[j][1]) + o3);
        }
        const int mi = lane >> 3, rr = lane & 7;
#pragma unroll
        for (int j = 0; j < 8; j += 2) {
            const int row = rr + 8 * (mi & 1);
            const int chunk = j + (mi >> 1);
            stmatrix_x4(stg + row * 128 + ((chunk ^ (row & 7)) * 16), po[j][0], po[j][1], po[j + 1][0], po[j + 1][1]);
        }
        __syncwarp();
        const size_t obase = (size_t)(row2 + 16 * warp) * D_ + c0 + 64 * rank;
#pragma unroll
        for (int i = 0; i < 4; i++) {
            const int row = 4 * i + (lane >> 3), chunk = lane & 7;
            uint4 v;
            asm volatile("ld.shared.v4.u32 {%0,%1,%2,%3}, [%4];" : "=r"(v.x), "=r"(v.y), "=r"(v.z), "=r"(v.w) : "r"(stg + row * 128 + ((chunk ^ (row & 7)) * 16)));
            *reinterpret_cast<uint4*>(out + obase + (size_t)row * D_ + chunk * 8) = v;
        }
        TS(2, 3 + wg, (tid & 127) == 0);
        if (warp == 0) {
            unsigned int last = 0;
            if (lane == 0) last = (atomicAdd(&g_c3, 1u) == 127u);
            last = __shfl_sync(0xffffffffu, last, 0);
            if (last) {
                reinterpret_cast<uint4*>(g_c2)[lane] = make_uint4(0u, 0u, 0u, 0u);
                if (lane == 0) { g_c1 = 0u; g_c3 = 0u; }
            }
        }
        }
    }
}

typedef CUresult (*PFN_encodeTiled)(CUtensorMap*, CUtensorMapDataType, cuuint32_t, void*, const cuuint64_t*, const cuuint64_t*,
                                    const cuuint32_t*, const cuuint32_t*, CUtensorMapInterleave, CUtensorMapSwizzle,
                                    CUtensorMapL2promotion, CUtensorMapFloatOOBfill);

static void make_map(PFN_encodeTiled enc, CUtensorMap* m, const void* ptr, uint64_t inner, uint64_t outer, uint32_t box_inner, uint32_t box_outer,
                     CUtensorMapSwizzle swz = CU_TENSOR_MAP_SWIZZLE_128B) {
    cuuint64_t dims[2] = {inner, outer};
    cuuint64_t strides[1] = {inner * 2};
    cuuint32_t box[2] = {box_inner, box_outer};
    cuuint32_t es[2] = {1, 1};
    enc(m, CU_TENSOR_MAP_DATA_TYPE_BFLOAT16, 2, const_cast<void*>(ptr), dims, strides, box, es, CU_TENSOR_MAP_INTERLEAVE_NONE,
        swz, CU_TENSOR_MAP_L2_PROMOTION_L2_256B, CU_TENSOR_MAP_FLOAT_OOB_FILL_NONE);
}

extern "C" void kernel_launch(void* const* d_in, const int* in_sizes, int n_in, void* d_out, int out_size) {
    const bf16* A_q = (const bf16*)d_in[0];
    const bf16* A_k = (const bf16*)d_in[1];
    const bf16* A_v = (const bf16*)d_in[2];
    const bf16* A_shift = (const bf16*)d_in[3];
    const bf16* A_ssmk = (const bf16*)d_in[4];
    const bf16* A_ssmD = (const bf16*)d_in[5];
    const bf16* w_gate = (const bf16*)d_in[7];
    const bf16* w_up = (const bf16*)d_in[8];
    const bf16* w_down = (const bf16*)d_in[9];

    static bool init = false;
    static CUtensorMap map_g, map_u, map_g32, map_u32, map_d, map_d32, map_k, map_kh, map_v, map_x;
    static const void* cached[6] = {nullptr, nullptr, nullptr, nullptr, nullptr, nullptr};
    if (!init || cached[0] != w_gate || cached[1] != w_up || cached[2] != w_down || cached[3] != A_q || cached[4] != A_k || cached[5] != A_v) {
        void* fn = nullptr;
        cudaDriverEntryPointQueryResult qres;
        cudaGetDriverEntryPoint("cuTensorMapEncodeTiled", &fn, cudaEnableDefault, &qres);
        PFN_encodeTiled enc = (PFN_encodeTiled)fn;
        make_map(enc, &map_g, w_gate, F_, D_, 64, 64);
        make_map(enc, &map_u, w_up, F_, D_, 64, 64);
        make_map(enc, &map_g32, w_gate, F_, D_, 32, 64, CU_TENSOR_MAP_SWIZZLE_64B);
        make_map(enc, &map_u32, w_up, F_, D_, 32, 64, CU_TENSOR_MAP_SWIZZLE_64B);
        make_map(enc, &map_d, w_down, D_, F_, 64, 64);
        make_map(enc, &map_d32, w_down, D_, F_, 64, 32);
        make_map(enc, &map_k, A_k, D_, S_, 8, 256, CU_TENSOR_MAP_SWIZZLE_NONE);
        make_map(enc, &map_kh, A_k, D_, S_, 8, 8, CU_TENSOR_MAP_SWIZZLE_NONE);
        make_map(enc, &map_v, A_v, D_, S_, 8, 256, CU_TENSOR_MAP_SWIZZLE_NONE);
        make_map(enc, &map_x, A_q, D_, S_, 8, 256, CU_TENSOR_MAP_SWIZZLE_NONE);
        cudaFuncSetAttribute(mega_kernel, cudaFuncAttributeMaxDynamicSharedMemorySize, SMEM_BYTES);
        cached[0] = w_gate; cached[1] = w_up; cached[2] = w_down; cached[3] = A_q; cached[4] = A_k; cached[5] = A_v;
        init = true;
    }
    mega_kernel<<<128, 512, SMEM_BYTES, cudaStreamPerThread>>>(A_q, A_k, A_v, A_shift, A_ssmk, A_ssmD, w_gate, w_up, w_down, (bf16*)d_out,
                                                               map_g, map_u, map_g32, map_u32, map_d, map_d32, map_k, map_kh, map_v, map_x);
}
```

```cpp
#include <cuda_runtime.h>
#include <cuda_bf16.h>
#include <cuda.h>
#include <stdint.h>

typedef __nv_bfloat16 bf16;
typedef __nv_bfloat162 bf162;

constexpr int S_ = 2048, D_ = 512, F_ = 1792;

__device__ __align__(1024) bf16 g_hb[S_ * D_];
__device__ __align__(1024) bf16 g_hh[S_ * F_];
__device__ __align__(128) uint32_t g_stats[S_];
__device__ unsigned int g_bar;
__device__ unsigned int g_c1;
__device__ __align__(16) unsigned int g_c2[128];
__device__ unsigned int g_c3;

#define TS_INIT()
#define TS_DUMP()
#define TS(k, i, cond)

__device__ __forceinline__ uint32_t smem_u32(const void* p) { return (uint32_t)__cvta_generic_to_shared(p); }

__device__ __forceinline__ void mbar_init(uint32_t bar, uint32_t count) {
    asm volatile("mbarrier.init.shared::cta.b64 [%0], %1;" ::"r"(bar), "r"(count) : "memory");
}
__device__ __forceinline__ void mbar_expect_tx(uint32_t bar, uint32_t bytes) {
    asm volatile("mbarrier.arrive.expect_tx.shared::cta.b64 _, [%0], %1;" ::"r"(bar), "r"(bytes) : "memory");
}
__device__ __forceinline__ void mbar_arrive(uint32_t bar) {
    asm volatile("mbarrier.arrive.shared::cta.b64 _, [%0];" ::"r"(bar) : "memory");
}
__device__ __forceinline__ uint32_t mapa(uint32_t addr, uint32_t rank) {
    uint32_t r;
    asm volatile("mapa.shared::cluster.u32 %0, %1, %2;" : "=r"(r) : "r"(addr), "r"(rank));
    return r;
}
__device__ __forceinline__ void mbar_arrive_cluster(uint32_t cluster_addr) {
    asm volatile("mbarrier.arrive.shared::cluster.b64 _, [%0];" ::"r"(cluster_addr) : "memory");
}
__device__ __forceinline__ void mbar_wait(uint32_t bar, uint32_t parity) {
    asm volatile(
        "{\n.reg .pred p;\n.reg .u32 c;\n"
        "mov.u32 c, 0;\n"
        "WAIT_%=:\n"
        "mbarrier.try_wait.parity.shared::cta.b64 p, [%0], %1;\n"
        "@p bra DONE_%=;\n"
        "add.u32 c, c, 1;\n"
        "setp.lt.u32 p, c, 4194304;\n"
        "@p bra WAIT_%=;\n"
        "DONE_%=:\n}\n"
        ::"r"(bar), "r"(parity) : "memory");
}
__device__ __forceinline__ void wait_counter(const unsigned int* p, unsigned int target) {
    unsigned int v, it = 0;
    do {
        asm volatile("ld.acquire.gpu.global.u32 %0, [%1];" : "=r"(v) : "l"(p) : "memory");
        if (++it > (1u << 24)) break;
    } while (v < target);
}
__device__ __forceinline__ void cluster_arrive() { asm volatile("barrier.cluster.arrive.release.aligned;" ::: "memory"); }
__device__ __forceinline__ void cluster_wait() { asm volatile("barrier.cluster.wait.acquire.aligned;" ::: "memory"); }
__device__ __forceinline__ void fence_proxy_async() { asm volatile("fence.proxy.async.shared::cta;" ::: "memory"); }
__device__ __forceinline__ void fence_proxy_async_global() { asm volatile("fence.proxy.async.global;" ::: "memory"); }
__device__ __forceinline__ void wgmma_fence() { asm volatile("wgmma.fence.sync.aligned;" ::: "memory"); }
__device__ __forceinline__ void wgmma_commit() { asm volatile("wgmma.commit_group.sync.aligned;" ::: "memory"); }
template <int N> __device__ __forceinline__ void wgmma_wait() { asm volatile("wgmma.wait_group.sync.aligned %0;" ::"n"(N) : "memory"); }

__device__ __forceinline__ void tma_load_2d(uint32_t dst, const CUtensorMap* map, uint32_t bar, int c0, int c1) {
    asm volatile(
        "cp.async.bulk.tensor.2d.shared::cluster.global.mbarrier::complete_tx::bytes [%0], [%1, {%3, %4}], [%2];"
        ::"r"(dst), "l"(map), "r"(bar), "r"(c0), "r"(c1) : "memory");
}
__device__ __forceinline__ void tma_load_2d_mc(uint32_t dst, const CUtensorMap* map, uint32_t bar, int c0, int c1, uint16_t mask) {
    asm volatile(
        "cp.async.bulk.tensor.2d.shared::cluster.global.mbarrier::complete_tx::bytes.multicast::cluster [%0], [%1, {%3, %4}], [%2], %5;"
        ::"r"(dst), "l"(map), "r"(bar), "r"(c0), "r"(c1), "h"(mask) : "memory");
}

__device__ __forceinline__ uint64_t make_desc(uint32_t addr, uint32_t lbo_bytes, uint32_t sbo_bytes, uint32_t swz) {
    uint64_t d = 0;
    d |= (uint64_t)((addr & 0x3FFFF) >> 4);
    d |= (uint64_t)((lbo_bytes & 0x3FFFF) >> 4) << 16;
    d |= (uint64_t)((sbo_bytes & 0x3FFFF) >> 4) << 32;
    d |= (uint64_t)swz << 62;
    return d;
}

__device__ __forceinline__ float bf16r(float x) { return __bfloat162float(__float2bfloat16_rn(x)); }
__device__ __forceinline__ uint32_t pack_bf16(float lo, float hi) {
    bf162 v = __floats2bfloat162_rn(lo, hi);
    return *reinterpret_cast<uint32_t*>(&v);
}
__device__ __forceinline__ float bf_lo(uint32_t u) { return __uint_as_float(u << 16); }
__device__ __forceinline__ float bf_hi(uint32_t u) { return __uint_as_float(u & 0xffff0000u); }
__device__ __forceinline__ void bf16r2(float& a, float& b) {
    const uint32_t p = pack_bf16(a, b);
    a = bf_lo(p); b = bf_hi(p);
}

__device__ __forceinline__ void stmatrix_x4(uint32_t addr, uint32_t r0, uint32_t r1, uint32_t r2, uint32_t r3) {
    asm volatile("stmatrix.sync.aligned.m8n8.x4.shared.b16 [%0], {%1,%2,%3,%4};" ::"r"(addr), "r"(r0), "r"(r1), "r"(r2), "r"(r3) : "memory");
}

template <int OFF>
__device__ __forceinline__ void wgmma_rs_n128(float* d, uint32_t a0, uint32_t a1, uint32_t a2, uint32_t a3, uint32_t dlo, uint32_t dhi) {
    asm volatile(
        "{\n.reg .b64 dsc;\n.reg .b32 lo;\nadd.s32 lo, %68, %70;\nmov.b64 dsc, {lo, %69};\n"
        "wgmma.mma_async.sync.aligned.m64n128k16.f32.bf16.bf16 "
        "{%0,%1,%2,%3,%4,%5,%6,%7,%8,%9,%10,%11,%12,%13,%14,%15,%16,%17,%18,%19,%20,%21,%22,%23,%24,%25,%26,%27,%28,%29,%30,%31,%32,%33,%34,%35,%36,%37,%38,%39,%40,%41,%42,%43,%44,%45,%46,%47,%48,%49,%50,%51,%52,%53,%54,%55,%56,%57,%58,%59,%60,%61,%62,%63}, {%64,%65,%66,%67}, dsc, 1, 1, 1, 0;\n}\n"
        : "+f"(d[0]), "+f"(d[1]), "+f"(d[2]), "+f"(d[3]), "+f"(d[4]), "+f"(d[5]), "+f"(d[6]), "+f"(d[7]), "+f"(d[8]), "+f"(d[9]), "+f"(d[10]), "+f"(d[11]), "+f"(d[12]), "+f"(d[13]), "+f"(d[14]), "+f"(d[15]), "+f"(d[16]), "+f"(d[17]), "+f"(d[18]), "+f"(d[19]), "+f"(d[20]), "+f"(d[21]), "+f"(d[22]), "+f"(d[23]), "+f"(d[24]), "+f"(d[25]), "+f"(d[26]), "+f"(d[27]), "+f"(d[28]), "+f"(d[29]), "+f"(d[30]), "+f"(d[31]), "+f"(d[32]), "+f"(d[33]), "+f"(d[34]), "+f"(d[35]), "+f"(d[36]), "+f"(d[37]), "+f"(d[38]), "+f"(d[39]), "+f"(d[40]), "+f"(d[41]), "+f"(d[42]), "+f"(d[43]), "+f"(d[44]), "+f"(d[45]), "+f"(d[46]), "+f"(d[47]), "+f"(d[48]), "+f"(d[49]), "+f"(d[50]), "+f"(d[51]), "+f"(d[52]), "+f"(d[53]), "+f"(d[54]), "+f"(d[55]), "+f"(d[56]), "+f"(d[57]), "+f"(d[58]), "+f"(d[59]), "+f"(d[60]), "+f"(d[61]), "+f"(d[62]), "+f"(d[63])
        : "r"(a0), "r"(a1), "r"(a2), "r"(a3), "r"(dlo), "r"(dhi), "n"(OFF));
}
template <int OFF>
__device__ __forceinline__ void wgmma_rs_n96(float* d, uint32_t a0, uint32_t a1, uint32_t a2, uint32_t a3, uint32_t dlo, uint32_t dhi) {
    asm volatile(
        "{\n.reg .b64 dsc;\n.reg .b32 lo;\nadd.s32 lo, %52, %54;\nmov.b64 dsc, {lo, %53};\n"
        "wgmma.mma_async.sync.aligned.m64n96k16.f32.bf16.bf16 "
        "{%0,%1,%2,%3,%4,%5,%6,%7,%8,%9,%10,%11,%12,%13,%14,%15,%16,%17,%18,%19,%20,%21,%22,%23,%24,%25,%26,%27,%28,%29,%30,%31,%32,%33,%34,%35,%36,%37,%38,%39,%40,%41,%42,%43,%44,%45,%46,%47}, {%48,%49,%50,%51}, dsc, 1, 1, 1, 0;\n}\n"
        : "+f"(d[0]), "+f"(d[1]), "+f"(d[2]), "+f"(d[3]), "+f"(d[4]), "+f"(d[5]), "+f"(d[6]), "+f"(d[7]), "+f"(d[8]), "+f"(d[9]), "+f"(d[10]), "+f"(d[11]), "+f"(d[12]), "+f"(d[13]), "+f"(d[14]), "+f"(d[15]), "+f"(d[16]), "+f"(d[17]), "+f"(d[18]), "+f"(d[19]), "+f"(d[20]), "+f"(d[21]), "+f"(d[22]), "+f"(d[23]), "+f"(d[24]), "+f"(d[25]), "+f"(d[26]), "+f"(d[27]), "+f"(d[28]), "+f"(d[29]), "+f"(d[30]), "+f"(d[31]), "+f"(d[32]), "+f"(d[33]), "+f"(d[34]), "+f"(d[35]), "+f"(d[36]), "+f"(d[37]), "+f"(d[38]), "+f"(d[39]), "+f"(d[40]), "+f"(d[41]), "+f"(d[42]), "+f"(d[43]), "+f"(d[44]), "+f"(d[45]), "+f"(d[46]), "+f"(d[47])
        : "r"(a0), "r"(a1), "r"(a2), "r"(a3), "r"(dlo), "r"(dhi), "n"(OFF));
}
template <int OFF>
__device__ __forceinline__ void wgmma_rs_n64(float* d, uint32_t a0, uint32_t a1, uint32_t a2, uint32_t a3, uint32_t dlo, uint32_t dhi) {
    asm volatile(
        "{\n.reg .b64 dsc;\n.reg .b32 lo;\nadd.s32 lo, %36, %38;\nmov.b64 dsc, {lo, %37};\n"
        "wgmma.mma_async.sync.aligned.m64n64k16.f32.bf16.bf16 "
        "{%0,%1,%2,%3,%4,%5,%6,%7,%8,%9,%10,%11,%12,%13,%14,%15,%16,%17,%18,%19,%20,%21,%22,%23,%24,%25,%26,%27,%28,%29,%30,%31}, {%32,%33,%34,%35}, dsc, 1, 1, 1, 0;\n}\n"
        : "+f"(d[0]), "+f"(d[1]), "+f"(d[2]), "+f"(d[3]), "+f"(d[4]), "+f"(d[5]), "+f"(d[6]), "+f"(d[7]), "+f"(d[8]), "+f"(d[9]), "+f"(d[10]), "+f"(d[11]), "+f"(d[12]), "+f"(d[13]), "+f"(d[14]), "+f"(d[15]), "+f"(d[16]), "+f"(d[17]), "+f"(d[18]), "+f"(d[19]), "+f"(d[20]), "+f"(d[21]), "+f"(d[22]), "+f"(d[23]), "+f"(d[24]), "+f"(d[25]), "+f"(d[26]), "+f"(d[27]), "+f"(d[28]), "+f"(d[29]), "+f"(d[30]), "+f"(d[31])
        : "r"(a0), "r"(a1), "r"(a2), "r"(a3), "r"(dlo), "r"(dhi), "n"(OFF));
}
template <int OFF>
__device__ __forceinline__ void wgmma_rs_n32(float* d, uint32_t a0, uint32_t a1, uint32_t a2, uint32_t a3, uint32_t dlo, uint32_t dhi) {
    asm volatile(
        "{\n.reg .b64 dsc;\n.reg .b32 lo;\nadd.s32 lo, %20, %22;\nmov.b64 dsc, {lo, %21};\n"
        "wgmma.mma_async.sync.aligned.m64n32k16.f32.bf16.bf16 "
        "{%0,%1,%2,%3,%4,%5,%6,%7,%8,%9,%10,%11,%12,%13,%14,%15}, {%16,%17,%18,%19}, dsc, 1, 1, 1, 0;\n}\n"
        : "+f"(d[0]), "+f"(d[1]), "+f"(d[2]), "+f"(d[3]), "+f"(d[4]), "+f"(d[5]), "+f"(d[6]), "+f"(d[7]), "+f"(d[8]), "+f"(d[9]), "+f"(d[10]), "+f"(d[11]), "+f"(d[12]), "+f"(d[13]), "+f"(d[14]), "+f"(d[15])
        : "r"(a0), "r"(a1), "r"(a2), "r"(a3), "r"(dlo), "r"(dhi), "n"(OFF));
}
template <int OFF>
__device__ __forceinline__ void wgmma_rs_n8(float* d, uint32_t a0, uint32_t a1, uint32_t a2, uint32_t a3, uint32_t dlo, uint32_t dhi) {
    asm volatile(
        "{\n.reg .b64 dsc;\n.reg .b32 lo;\nadd.s32 lo, %8, %10;\nmov.b64 dsc, {lo, %9};\n"
        "wgmma.mma_async.sync.aligned.m64n8k16.f32.bf16.bf16 "
        "{%0,%1,%2,%3}, {%4,%5,%6,%7}, dsc, 1, 1, 1, 0;\n}\n"
        : "+f"(d[0]), "+f"(d[1]), "+f"(d[2]), "+f"(d[3])
        : "r"(a0), "r"(a1), "r"(a2), "r"(a3), "r"(dlo), "r"(dhi), "n"(OFF));
}
template <int OFF>
__device__ __forceinline__ void wgmma_rst_n128(float* d, const uint32_t* a, uint32_t dlo, uint32_t dhi) {
    asm volatile(
        "{\n.reg .b64 dsc;\n.reg .b32 lo;\nadd.s32 lo, %68, %70;\nmov.b64 dsc, {lo, %69};\n"
        "wgmma.mma_async.sync.aligned.m64n128k16.f32.bf16.bf16 "
        "{%0,%1,%2,%3,%4,%5,%6,%7,%8,%9,%10,%11,%12,%13,%14,%15,%16,%17,%18,%19,%20,%21,%22,%23,%24,%25,%26,%27,%28,%29,%30,%31,%32,%33,%34,%35,%36,%37,%38,%39,%40,%41,%42,%43,%44,%45,%46,%47,%48,%49,%50,%51,%52,%53,%54,%55,%56,%57,%58,%59,%60,%61,%62,%63}, {%64,%65,%66,%67}, dsc, 1, 1, 1, 1;\n}\n"
        : "+f"(d[0]), "+f"(d[1]), "+f"(d[2]), "+f"(d[3]), "+f"(d[4]), "+f"(d[5]), "+f"(d[6]), "+f"(d[7]), "+f"(d[8]), "+f"(d[9]), "+f"(d[10]), "+f"(d[11]), "+f"(d[12]), "+f"(d[13]), "+f"(d[14]), "+f"(d[15]), "+f"(d[16]), "+f"(d[17]), "+f"(d[18]), "+f"(d[19]), "+f"(d[20]), "+f"(d[21]), "+f"(d[22]), "+f"(d[23]), "+f"(d[24]), "+f"(d[25]), "+f"(d[26]), "+f"(d[27]), "+f"(d[28]), "+f"(d[29]), "+f"(d[30]), "+f"(d[31]), "+f"(d[32]), "+f"(d[33]), "+f"(d[34]), "+f"(d[35]), "+f"(d[36]), "+f"(d[37]), "+f"(d[38]), "+f"(d[39]), "+f"(d[40]), "+f"(d[41]), "+f"(d[42]), "+f"(d[43]), "+f"(d[44]), "+f"(d[45]), "+f"(d[46]), "+f"(d[47]), "+f"(d[48]), "+f"(d[49]), "+f"(d[50]), "+f"(d[51]), "+f"(d[52]), "+f"(d[53]), "+f"(d[54]), "+f"(d[55]), "+f"(d[56]), "+f"(d[57]), "+f"(d[58]), "+f"(d[59]), "+f"(d[60]), "+f"(d[61]), "+f"(d[62]), "+f"(d[63])
        : "r"(a[0]), "r"(a[1]), "r"(a[2]), "r"(a[3]), "r"(dlo), "r"(dhi), "n"(OFF));
}
template <int OFF>
__device__ __forceinline__ void wgmma_rst_n64(float* d, const uint32_t* a, uint32_t dlo, uint32_t dhi) {
    asm volatile(
        "{\n.reg .b64 dsc;\n.reg .b32 lo;\nadd.s32 lo, %36, %38;\nmov.b64 dsc, {lo, %37};\n"
        "wgmma.mma_async.sync.aligned.m64n64k16.f32.bf16.bf16 "
        "{%0,%1,%2,%3,%4,%5,%6,%7,%8,%9,%10,%11,%12,%13,%14,%15,%16,%17,%18,%19,%20,%21,%22,%23,%24,%25,%26,%27,%28,%29,%30,%31}, {%32,%33,%34,%35}, dsc, 1, 1, 1, 1;\n}\n"
        : "+f"(d[0]), "+f"(d[1]), "+f"(d[2]), "+f"(d[3]), "+f"(d[4]), "+f"(d[5]), "+f"(d[6]), "+f"(d[7]), "+f"(d[8]), "+f"(d[9]), "+f"(d[10]), "+f"(d[11]), "+f"(d[12]), "+f"(d[13]), "+f"(d[14]), "+f"(d[15]), "+f"(d[16]), "+f"(d[17]), "+f"(d[18]), "+f"(d[19]), "+f"(d[20]), "+f"(d[21]), "+f"(d[22]), "+f"(d[23]), "+f"(d[24]), "+f"(d[25]), "+f"(d[26]), "+f"(d[27]), "+f"(d[28]), "+f"(d[29]), "+f"(d[30]), "+f"(d[31])
        : "r"(a[0]), "r"(a[1]), "r"(a[2]), "r"(a[3]), "r"(dlo), "r"(dhi), "n"(OFF));
}

constexpr int NSLOT = 14;
constexpr int SLOT = 16384;
constexpr int X_OFF = 10 * SLOT;
constexpr int BAR_OFF = NSLOT * SLOT;
constexpr int ONES_OFF = BAR_OFF + 512;
constexpr int SMEM_BYTES = BAR_OFF + 800 + 1024;
constexpr int PRE = 3;
constexpr int G1_LAG = 4;
constexpr int A_SLOT0 = 6;
constexpr int CV_BASE = PRE * SLOT;
constexpr int CV_R = 156;
constexpr int CV_XT_BYTES = 2 * CV_R * 16;
constexpr int CV_WT_BYTES = 2064 * 4;
constexpr int CV_P_BYTES = 3072 * 4;
constexpr int CV_CH_BYTES = CV_XT_BYTES + CV_WT_BYTES + 2 * CV_P_BYTES + 80;
static_assert(CV_CH_BYTES % 128 == 16, "channel pitch");
constexpr int CV_XS_OFF = CV_BASE + 4 * CV_CH_BYTES;
constexpr int CV_XS_PITCH = 4096 + 16;
constexpr int CV_ST_OFF = CV_XS_OFF + 4 * CV_XS_PITCH;
static_assert(CV_XS_OFF % 16 == 0 && CV_ST_OFF % 16 == 0 && CV_ST_OFF + 8192 <= BAR_OFF, "conv layout");
constexpr int cv_stage(int c) { return (CV_BASE + c * CV_CH_BYTES + CV_XT_BYTES + CV_WT_BYTES + 1023) / 1024 * 1024; }
constexpr int CV_KS_OFF = cv_stage(0), CV_VS_OFF = cv_stage(1), CV_XI_OFF = cv_stage(2);
static_assert(CV_KS_OFF + 1024 + 16384 <= CV_BASE + CV_CH_BYTES && CV_VS_OFF + 16384 <= CV_BASE + 2 * CV_CH_BYTES && CV_XI_OFF + 16384 <= CV_BASE + 3 * CV_CH_BYTES, "staging");

__device__ __forceinline__ void conv_load(uint32_t (&w)[6], const uint32_t* wp) {
#pragma unroll
    for (int s = 0; s < 2; s++) { w[3 * s] = wp[64 * s - 8]; w[3 * s + 1] = wp[64 * s]; w[3 * s + 2] = wp[64 * s + 8]; }
}
template <int L, int OFF>
__device__ __forceinline__ void conv_mma1(float* acc, uint32_t a2, uint32_t a0, uint32_t a1, uint32_t dlo, uint32_t dhi) {
    if (L == 0) wgmma_rs_n128<OFF>(acc, a0, a1, a2, a0, dlo, dhi);
    else if (L == 1) wgmma_rs_n128<OFF>(acc, a0, a1, a2, a0, dlo, dhi);
    else if (L == 2) wgmma_rs_n96<OFF>(acc, a0, a1, a2, a0, dlo, dhi);
    else if (L == 3) wgmma_rs_n96<OFF>(acc, a0, a1, a2, a0, dlo, dhi);
    else if (L == 4) wgmma_rs_n64<OFF>(acc, a0, a1, a2, a0, dlo, dhi);
    else if (L == 5) wgmma_rs_n64<OFF>(acc, a0, a1, a2, a0, dlo, dhi);
    else if (L == 6) wgmma_rs_n32<OFF>(acc, a0, a1, a2, a0, dlo, dhi);
    else wgmma_rs_n32<OFF>(acc, a0, a1, a2, a0, dlo, dhi);
}
template <int B>
__device__ __forceinline__ void conv_issue(float* acc, const uint32_t (&w)[6], uint32_t dlo, uint32_t dhi) {
    wgmma_fence();
    conv_mma1<(B >> 1), 8 * B + 0>(acc, w[0], w[1], w[2], dlo, dhi);
    conv_mma1<(B >> 1), 8 * B + 4>(acc, w[3], w[4], w[5], dlo, dhi);
    wgmma_commit();
}
template <int B>
__device__ __forceinline__ void conv_pair(float* acc, uint32_t (&q0)[6], uint32_t (&q1)[6], const uint32_t* wp, uint32_t dlo, uint32_t dhi) {
    if (B > 0 && (B & 3) == 0) wgmma_wait<0>();
    conv_issue<B>(acc, q0, dlo, dhi);
    if ((B & 3) != 0) wgmma_wait<1>();
    conv_load(q1, wp + 128 * (B + 1));
    conv_issue<B + 1>(acc, q1, dlo, dhi);
    if (B + 2 < 16) {
        wgmma_wait<1>();
        conv_load(q0, wp + 128 * (B + 2));
    }
}
__device__ __forceinline__ void conv_mma(float* acc, const uint32_t* wp, uint32_t xt_base) {
    uint32_t q0[6], q1[6];
    const uint64_t desc0 = make_desc(xt_base, CV_R * 16, 128, 0);
    const uint32_t dlo = (uint32_t)desc0, dhi = (uint32_t)(desc0 >> 32);
    conv_load(q0, wp);
    conv_pair<0>(acc, q0, q1, wp, dlo, dhi);
    conv_pair<2>(acc, q0, q1, wp, dlo, dhi);
    conv_pair<4>(acc, q0, q1, wp, dlo, dhi);
    conv_pair<6>(acc, q0, q1, wp, dlo, dhi);
    conv_pair<8>(acc, q0, q1, wp, dlo, dhi);
    conv_pair<10>(acc, q0, q1, wp, dlo, dhi);
    conv_pair<12>(acc, q0, q1, wp, dlo, dhi);
    conv_pair<14>(acc, q0, q1, wp, dlo, dhi);
    wgmma_wait<0>();
}
__device__ __forceinline__ float warp_sum(float v) {
#pragma unroll
    for (int o = 16; o > 0; o >>= 1) v += __shfl_xor_sync(0xffffffffu, v, o);
    return v;
}
__device__ __forceinline__ float sigmoid_f(float x) {
    float e, r;
    asm("ex2.approx.ftz.f32 %0, %1;" : "=f"(e) : "f"(x * -1.4426950408889634f));
    asm("rcp.approx.ftz.f32 %0, %1;" : "=f"(r) : "f"(1.f + e));
    return r;
}
__device__ __forceinline__ void st_async_v4(uint32_t addr, const uint32_t (&c)[4], uint32_t bar) {
    asm volatile("st.async.weak.shared::cluster.mbarrier::complete_tx::bytes.v4.b32 [%0], {%1,%2,%3,%4}, [%5];"
                 ::"r"(addr), "r"(c[0]), "r"(c[1]), "r"(c[2]), "r"(c[3]), "r"(bar) : "memory");
}

__device__ __forceinline__ void load_chunk_t(uint32_t addr_rows, int lane, uint32_t (&r)[4]) {
    asm volatile("ldmatrix.sync.aligned.m8n8.x4.trans.shared.b16 {%0,%1,%2,%3}, [%4];"
                 : "=r"(r[0]), "=r"(r[1]), "=r"(r[2]), "=r"(r[3]) : "r"(addr_rows + lane * 16) : "memory");
    const bool b0 = lane & 1, b1 = lane & 2;
    uint32_t x, y;
    x = b0 ? r[0] : r[1]; y = b0 ? r[2] : r[3];
    x = __shfl_xor_sync(0xffffffffu, x, 1); y = __shfl_xor_sync(0xffffffffu, y, 1);
    if (b0) { r[0] = x; r[2] = y; } else { r[1] = x; r[3] = y; }
    x = b1 ? r[0] : r[2]; y = b1 ? r[1] : r[3];
    x = __shfl_xor_sync(0xffffffffu, x, 2); y = __shfl_xor_sync(0xffffffffu, y, 2);
    if (b1) { r[0] = x; r[1] = y; } else { r[2] = x; r[3] = y; }
}

template <bool FULL>
__device__ __forceinline__ void gemm1_pass(int T, const uint32_t (&a)[32][4], float inv0, float inv1, uint32_t sb, uint32_t peer,
                                           int row0, int f0, int tid, int wg) {
    const int warp = tid >> 5, lane = tid & 31;
    const uint32_t barFull = sb + BAR_OFF, barEmpty = barFull + 8 * NSLOT;
    const uint64_t d0_ = FULL ? make_desc(sb, 8192, 1024, 1) : make_desc(sb, 4096, 512, 2);
    const uint32_t dlo0 = (uint32_t)d0_, dhi = (uint32_t)(d0_ >> 32);
    const uint32_t peerEmpty = mapa(barEmpty, peer);
    int st = (T * 8) % NSLOT, ph = ((T * 8) / NSLOT) & 1;
    constexpr int UO = FULL ? 32 : 16;
    float acc[2 * UO];
#pragma unroll
    for (int i = 0; i < 2 * UO; i++) acc[i] = 0.f;
#pragma unroll
    for (int kb = 0; kb < 8; kb++) {
        mbar_wait(barFull + 8 * st, ph);
        wgmma_fence();
        const uint32_t dlo = dlo0 + st * (SLOT / 16);
        if (FULL) {
            wgmma_rst_n128<0>(acc, a[4 * kb], dlo, dhi); wgmma_rst_n128<128>(acc, a[4 * kb + 1], dlo, dhi);
            wgmma_rst_n128<256>(acc, a[4 * kb + 2], dlo, dhi); wgmma_rst_n128<384>(acc, a[4 * kb + 3], dlo, dhi);
        } else {
            wgmma_rst_n64<0>(acc, a[4 * kb], dlo, dhi); wgmma_rst_n64<64>(acc, a[4 * kb + 1], dlo, dhi);
            wgmma_rst_n64<128>(acc, a[4 * kb + 2], dlo, dhi); wgmma_rst_n64<192>(acc, a[4 * kb + 3], dlo, dhi);
        }
        wgmma_commit();
        if (kb == G1_LAG) asm volatile("{\n.reg .pred p;\nsetp.eq.s32 p, %0, 0;\n@p bar.arrive 5, 256;\n}\n" ::"r"(wg + T) : "memory");
        if (kb > 0) {
            wgmma_wait<1>();
            if ((tid & 127) == 0) {
                const int pst = (st == 0) ? NSLOT - 1 : st - 1;
                mbar_arrive(barEmpty + 8 * pst);
                mbar_arrive_cluster(peerEmpty + 8 * pst);
            }
        }
        if (++st == NSLOT) { st = 0; ph ^= 1; }
    }
    wgmma_wait<0>();
    if ((tid & 127) == 0) {
        const int pst = (st == 0) ? NSLOT - 1 : st - 1;
        mbar_arrive(barEmpty + 8 * pst);
        mbar_arrive_cluster(peerEmpty + 8 * pst);
    }
    TS(1, 3 + 2 * T, tid == 0);
    TS(2, 12 + T, tid == 128);
    constexpr int NJ = FULL ? 8 : 4;
    uint32_t pk[NJ][2];
#pragma unroll
    for (int j = 0; j < NJ; j++) {
#pragma unroll
        for (int hf = 0; hf < 2; hf++) {
            const float inv = hf ? inv1 : inv0;
            const uint32_t gp = pack_bf16(acc[4 * j + 2 * hf] * inv, acc[4 * j + 2 * hf + 1] * inv);
            const uint32_t up = pack_bf16(acc[UO + 4 * j + 2 * hf] * inv, acc[UO + 4 * j + 2 * hf + 1] * inv);
            const uint32_t sp = pack_bf16(sigmoid_f(bf_lo(gp)), sigmoid_f(bf_hi(gp)));
            const bf162 pr = __hmul2_rn(*reinterpret_cast<const bf162*>(&sp), *reinterpret_cast<const bf162*>(&up));
            pk[j][hf] = *reinterpret_cast<const uint32_t*>(&pr);
        }
    }
    const int ns = f0;
    const int blk = 14 * (ns >> 2) + (FULL ? 4 * T + (ns & 3) : 12 + ((ns & 3) >> 1));
    uint4* dst = reinterpret_cast<uint4*>(g_hh) + ((size_t)(row0 >> 7) * 28 + blk) * 1024 + warp * 128 + (FULL ? 0 : (ns & 1) * 64) + lane;
#pragma unroll
    for (int j = 0; j < NJ; j += 2) dst[(j >> 1) * 32] = make_uint4(pk[j][0], pk[j][1], pk[j + 1][0], pk[j + 1][1]);
    asm volatile("bar.arrive %0, 160;" ::"r"(11 + wg) : "memory");
    TS(1, 4 + 2 * T, tid == 0);
}

constexpr int NA = 6;
__device__ __forceinline__ int g2_slotB(int j) { return 4 + (j & 7); }
__device__ __forceinline__ int g2_fillB(int j) { return 2 + (j >> 3); }
__device__ __forceinline__ int g2_slotA(int j) { return (12 + j % NA) % NSLOT; }
__device__ __forceinline__ int g2_fillA(int j) { return (j % NA < 2 ? 2 : 3) + j / NA; }

__global__ void __cluster_dims__(2, 1, 1) __launch_bounds__(512, 1)
mega_kernel(const bf16* __restrict__ xin, const bf16* __restrict__ kin, const bf16* __restrict__ vin, const bf16* __restrict__ shift_k,
            const bf16* __restrict__ ssm_k, const bf16* __restrict__ ssm_D,
            const bf16* __restrict__ w_gate, const bf16* __restrict__ w_up, const bf16* __restrict__ w_down, bf16* __restrict__ out,
            const __grid_constant__ CUtensorMap map_g, const __grid_constant__ CUtensorMap map_u,
            const __grid_constant__ CUtensorMap map_g32, const __grid_constant__ CUtensorMap map_u32,
            const __grid_constant__ CUtensorMap map_d, const __grid_constant__ CUtensorMap map_d32, const __grid_constant__ CUtensorMap map_k, const __grid_constant__ CUtensorMap map_kh,
            const __grid_constant__ CUtensorMap map_v, const __grid_constant__ CUtensorMap map_x) {
    extern __shared__ uint8_t smem_raw[];
    uint8_t* smem = smem_raw + ((1024u - (smem_u32(smem_raw) & 1023u)) & 1023u);
    const uint32_t sb = smem_u32(smem);
    const uint32_t barFull = sb + BAR_OFF, barEmpty = barFull + 8 * NSLOT, barA = barEmpty + 8 * NSLOT;
    const uint32_t barKV = barA + 64, barXS = barKV + 8, barX = barXS + 8, barKin = barX + 8, barXin = barKin + 8, barAE = barXin + 8, barG1 = barAE + 48, barRdy = barG1 + 8, barKi = barRdy + 8;
    const int tid = threadIdx.x, warp = tid >> 5, lane = tid & 31;
    const int bid = blockIdx.x;
    const int rank = bid & 1;
    const int d0 = bid * 4, dp = (bid >> 1) * 8;
    const int ns = (bid >> 1) & 7, mt1 = 2 * (bid >> 4) + rank;
    const int f0 = ns * 224;
    const int mt2 = bid >> 3, nt = (bid >> 1) & 3;
    TS_INIT();
    TS(0, 0, tid == 0);

    if (tid == 0) {
        for (int i = 0; i < NSLOT; i++) { mbar_init(barFull + 8 * i, 1); mbar_init(barEmpty + 8 * i, 4); }
        for (int i = 0; i < 8; i++) mbar_init(barA + 8 * i, 1);
        mbar_init(barKV, 1);
        mbar_init(barXS, 2);
        mbar_init(barX, 1);
        for (int i = 0; i < NA; i++) mbar_init(barAE + 8 * i, 8);
        mbar_init(barRdy, 2);
        *reinterpret_cast<volatile unsigned int*>(smem + ONES_OFF + 256) = 0u;
        mbar_init(barG1, 1);
        for (int i = 0; i < 4; i++) mbar_init(barKi + 8 * i, 1);
        mbar_init(barKin, 1);
        mbar_init(barXin, 1);
        asm volatile("fence.mbarrier_init.release.cluster;" ::: "memory");
        mbar_expect_tx(barKV, 16384);
        mbar_expect_tx(barXS, 16384);
        mbar_expect_tx(barX, 32768);
        for (int i = 0; i < 4; i++) {
            mbar_expect_tx(barKi + 8 * i, i == 0 ? 8192 + 128 : 8192);
            if (i == 0) tma_load_2d(sb + CV_KS_OFF + 896, &map_kh, barKi, dp, 1024 * rank - 8);
            tma_load_2d(sb + CV_KS_OFF + 1024 + i * 4096, &map_k, barKi + 8 * i, dp, 1024 * rank + 256 * i);
            tma_load_2d(sb + CV_VS_OFF + i * 4096, &map_v, barKi + 8 * i, dp, 1024 * rank + 256 * i);
        }
        mbar_expect_tx(barXin, 16384);
        for (int i = 0; i < 4; i++) tma_load_2d(sb + CV_XI_OFF + i * 4096, &map_x, barXin, dp, 1024 * rank + 256 * i);
    }
    __syncwarp();
    asm volatile("barrier.cluster.arrive.relaxed.aligned;" ::: "memory");
    const uint2 dD = __ldg(reinterpret_cast<const uint2*>(ssm_D + d0));

    if (tid < 256) {
        uint32_t w[4][4];
#pragma unroll
        for (int cp = 0; cp < 4; cp++) {
            const uint4 sw = __ldg(reinterpret_cast<const uint4*>(shift_k + (dp + 2 * cp) * 4));
            w[0][cp] = __byte_perm(sw.x, sw.z, 0x5410); w[1][cp] = __byte_perm(sw.x, sw.z, 0x7632);
            w[2][cp] = __byte_perm(sw.y, sw.w, 0x5410); w[3][cp] = __byte_perm(sw.y, sw.w, 0x7632);
        }
        asm volatile("bar.sync 1, 512;" ::: "memory");
        cluster_wait();
        const int g = lane >> 2, t = lane & 3;
        const uint32_t dbase = mapa(sb, g >> 2);
#pragma unroll 1
        for (int i = 0; i < 4; i++) {
            mbar_wait(barKi + 8 * i, 0);
            const int row = tid + 256 * i;
            const uint4* ks = reinterpret_cast<const uint4*>(smem + CV_KS_OFF + 1024) + row;
            uint4* vs = reinterpret_cast<uint4*>(smem + CV_VS_OFF) + row;
            const uint4 k0 = ks[-3], k1 = ks[-2], k2 = ks[-1], k3 = ks[0], vv = vs[0];
            const uint32_t ka[4][4] = {{k0.x, k0.y, k0.z, k0.w}, {k1.x, k1.y, k1.z, k1.w}, {k2.x, k2.y, k2.z, k2.w}, {k3.x, k3.y, k3.z, k3.w}};
            const uint32_t va[4] = {vv.x, vv.y, vv.z, vv.w};
            uint32_t o[4];
#pragma unroll
            for (int cp = 0; cp < 4; cp++) {
                bf162 acc2 = __hmul2_rn(*reinterpret_cast<const bf162*>(&ka[0][cp]), *reinterpret_cast<const bf162*>(&w[3][cp]));
#pragma unroll
                for (int t = 1; t < 4; t++)
                    acc2 = __hadd2_rn(acc2, __hmul2_rn(*reinterpret_cast<const bf162*>(&ka[t][cp]), *reinterpret_cast<const bf162*>(&w[3 - t][cp])));
                acc2 = __hmul2_rn(acc2, *reinterpret_cast<const bf162*>(&va[cp]));
                o[cp] = *reinterpret_cast<uint32_t*>(&acc2);
            }
            vs[0] = make_uint4(o[0], o[1], o[2], o[3]);
            __syncwarp();
            const int row0 = 32 * warp + 256 * i;
            uint32_t c[4];
            load_chunk_t(sb + CV_VS_OFF + row0 * 16, lane, c);
            const int p = 128 * rank + (row0 >> 3) + t;
            st_async_v4(dbase + CV_BASE + (g & 3) * CV_CH_BYTES + ((p & 1) * CV_R + 127 - (p >> 1)) * 16, c, dbase + BAR_OFF + (barKV - barFull));
        }
    } else {
        const int u = tid - 256;
        const int lrow = bid * 16 + 2 * (u >> 5);
        const uint4* xp = reinterpret_cast<const uint4*>(xin + (size_t)lrow * D_ + lane * 16);
        uint4 xa[2], xb[2];
        xa[0] = __ldg(xp); xb[0] = __ldg(xp + 1); xa[1] = __ldg(xp + 64); xb[1] = __ldg(xp + 65);
        uint4 kk[4]; uint32_t prev[4];
#pragma unroll
        for (int c = 0; c < 4; c++) {
            const bf16* kp = ssm_k + (size_t)(d0 + c) * S_ + 8 * u;
            kk[c] = __ldg(reinterpret_cast<const uint4*>(kp));
            prev[c] = (u > 0) ? (uint32_t)__ldg(reinterpret_cast<const unsigned short*>(kp - 1)) : 0u;
        }
        asm volatile("bar.sync 1, 512;" ::: "memory");
        if (u < 224) *reinterpret_cast<uint4*>(smem + CV_BASE + (u / 56) * CV_CH_BYTES + (((u % 56) / 28) * CV_R + 128 + (u % 28)) * 16) = make_uint4(0, 0, 0, 0);
        if (u < 64) reinterpret_cast<uint32_t*>(smem + CV_BASE + (u >> 4) * CV_CH_BYTES + CV_XT_BYTES)[u & 15] = 0;
        else if (u < 128) reinterpret_cast<uint32_t*>(smem + ONES_OFF)[u - 64] = 0x3F803F80u;
#pragma unroll
        for (int c = 0; c < 4; c++) {
            uint4 lo, hi;
            lo.x = (kk[c].x & 0xffffu) | (prev[c] << 16);
            lo.y = __byte_perm(kk[c].x, 0, 0x1032);
            lo.z = __byte_perm(kk[c].y, kk[c].x, 0x7610);
            lo.w = __byte_perm(kk[c].y, 0, 0x1032);
            hi.x = __byte_perm(kk[c].z, kk[c].y, 0x7610);
            hi.y = __byte_perm(kk[c].z, 0, 0x1032);
            hi.z = __byte_perm(kk[c].w, kk[c].z, 0x7610);
            hi.w = __byte_perm(kk[c].w, 0, 0x1032);
            uint4* dst = reinterpret_cast<uint4*>(smem + CV_BASE + c * CV_CH_BYTES + CV_XT_BYTES + (16 + 8 * u) * 4);
            dst[0] = lo; dst[1] = hi;
        }
        fence_proxy_async();
        __syncwarp();
        asm volatile("bar.arrive 2, 512;" ::: "memory");
        asm volatile("bar.sync 3, 256;" ::: "memory");
#pragma unroll
        for (int r = 0; r < 2; r++) {
            const uint32_t xw[8] = {xa[r].x, xa[r].y, xa[r].z, xa[r].w, xb[r].x, xb[r].y, xb[r].z, xb[r].w};
            float sm_ = 0.f;
#pragma unroll
            for (int i = 0; i < 8; i++) sm_ += bf_lo(xw[i]) + bf_hi(xw[i]);
            sm_ = warp_sum(sm_);
            const float mean = sm_ * (1.f / 512.f);
            float q = 0.f;
#pragma unroll
            for (int i = 0; i < 8; i++) { float d1 = bf_lo(xw[i]) - mean, d2 = bf_hi(xw[i]) - mean; q += d1 * d1 + d2 * d2; }
            q = warp_sum(q);
            if (lane == 0) {
                g_stats[lrow + r] = pack_bf16(mean, sqrtf(bf16r(bf16r(q * (1.f / 512.f)) + 1e-5f)));
            }
        }
        if (lane == 0) {
            __threadfence();
            const unsigned int old = atomicAdd(&g_bar, 1u);
            if (u == 0) *reinterpret_cast<volatile unsigned int*>(smem + ONES_OFF + 256) = (old / 1024u + 1u) * 1024u + 1u;
        }
        __syncwarp();
        cluster_wait();
        if (u == 32) {
            const CUtensorMap* mw = rank ? &map_u : &map_g;
            for (int it = 0; it < PRE; it++) {
                mbar_expect_tx(barFull + 8 * it, SLOT);
                tma_load_2d_mc(sb + it * SLOT + rank * 8192, mw, barFull + 8 * it, f0, 64 * it, (uint16_t)3);
            }
        }
    }
    TS(0, 1, tid == 0);
    mbar_wait(barKV, 0);
    fence_proxy_async();
    if (tid < 256) asm volatile("bar.sync 2, 512;" ::: "memory");

    const int wg = __shfl_sync(0xffffffffu, tid >> 7, 0);
    {
        const int wq = warp & 3, g = lane >> 2, t = lane & 3;
        uint8_t* chs = smem + CV_BASE + wg * CV_CH_BYTES;
        float acc[64];
#pragma unroll
        for (int i = 0; i < 64; i++) acc[i] = 0.f;
        const uint32_t* wp = reinterpret_cast<const uint32_t*>(chs + CV_XT_BYTES) + 16 + 16 * wq + g - 2 * t;
        conv_mma(acc, wp, smem_u32(chs));
        TS(0, 4 + wg, (tid & 127) == 0);
        if (wg < 2) {
            if (tid == 0) {
                unsigned int v;
                asm volatile("ld.acquire.gpu.global.u32 %0, [%1];" : "=r"(v) : "l"(&g_bar) : "memory");
                unsigned int target = 0;
                for (unsigned int it = 0; target == 0u && it < (1u << 22); it++) target = *reinterpret_cast<volatile unsigned int*>(smem + ONES_OFF + 256);
                target -= 1u;
                for (unsigned int it = 0; (int)(v - target) < 0 && it < (1u << 22); it++) asm volatile("ld.acquire.gpu.global.u32 %0, [%1];" : "=r"(v) : "l"(&g_bar) : "memory");
                fence_proxy_async_global();
                mbar_expect_tx(barXS, 8192);
                asm volatile("cp.async.bulk.shared::cluster.global.mbarrier::complete_tx::bytes [%0], [%1], %2, [%3];"
                             ::"r"(sb + CV_ST_OFF), "l"(g_stats), "r"(8192), "r"(barXS) : "memory");
                constexpr int SH = D_ * F_ * 2 / 128;
                asm volatile("cp.async.bulk.prefetch.L2.global [%0], %1;" ::"l"(reinterpret_cast<const uint8_t*>(w_gate) + (size_t)bid * SH), "r"(SH) : "memory");
                asm volatile("cp.async.bulk.prefetch.L2.global [%0], %1;" ::"l"(reinterpret_cast<const uint8_t*>(w_up) + (size_t)bid * SH), "r"(SH) : "memory");
                asm volatile("cp.async.bulk.prefetch.L2.global [%0], %1;" ::"l"(reinterpret_cast<const uint8_t*>(w_down) + (size_t)bid * SH), "r"(SH) : "memory");
            }
            __syncwarp();
        }
        if (wg < 2) {
            const uint32_t dbase = mapa(sb, g >> 2);
            mbar_wait(barXin, 0);
#pragma unroll
            for (int i = 0; i < 4; i++) {
                const int row0 = 32 * warp + 256 * i;
                uint32_t c[4];
                load_chunk_t(sb + CV_XI_OFF + row0 * 16, lane, c);
                const int p = 128 * rank + (row0 >> 3) + t;
                st_async_v4(dbase + CV_XS_OFF + (g & 3) * CV_XS_PITCH + p * 16, c, dbase + BAR_OFF + (barXS - barFull));
            }
            asm volatile("bar.arrive 10, 384;" ::: "memory");
        }
        if (wg == 2) asm volatile("bar.sync 10, 384;" ::: "memory");
        const uint32_t pbase = smem_u32(chs + CV_XT_BYTES + CV_WT_BYTES + (wq & 1) * CV_P_BYTES);
        uint32_t pa[4];
        bool ok0[4];
#pragma unroll
        for (int e = 0; e < 4; e++) {
            const int s = 16 * (127 - 2 * t) + 16 * wq + g - 16 * (e & 1) + 8 * (e >> 1);
            pa[e] = pbase + (s + 4 * (s >> 3)) * 4;
            ok0[e] = s < S_;
        }
        if (wq < 2) {
#pragma unroll
            for (int i = 0; i < 64; i++) {
                const int e = (i & 1) | (i & 2);
                if (i >= 4 || ok0[e]) asm volatile("st.shared.f32 [%0], %1;" ::"r"(pa[e] - 768 * (i >> 2)), "f"(acc[i]) : "memory");
            }
            if (wq == 1 && lane < 16) asm volatile("st.shared.f32 [%0], %1;" ::"r"(pbase + (lane + 4 * (lane >> 3)) * 4), "f"(0.f) : "memory");
        }
        asm volatile("bar.sync %0, 128;" ::"r"(6 + wg) : "memory");
        if (wq >= 2) {
#pragma unroll
            for (int i0 = 0; i0 < 64; i0 += 16) {
                float o[16];
#pragma unroll
                for (int i = i0; i < i0 + 16; i++) {
                    const int e = (i & 1) | (i & 2);
                    o[i - i0] = 0.f;
                    if (i >= 4 || ok0[e]) asm volatile("ld.shared.f32 %0, [%1];" : "=f"(o[i - i0]) : "r"(pa[e] - 768 * (i >> 2)));
                }
#pragma unroll
                for (int i = i0; i < i0 + 16; i++) {
                    const int e = (i & 1) | (i & 2);
                    if (i >= 4 || ok0[e]) asm volatile("st.shared.f32 [%0], %1;" ::"r"(pa[e] - 768 * (i >> 2)), "f"(o[i - i0] + acc[i]) : "memory");
                }
            }
        }
    }
    TS(0, 10, tid == 0);
    TS(0, 11, tid == 480);
    mbar_wait(barXS, 0);
    asm volatile("bar.sync %0, 128;" ::"r"(6 + wg) : "memory");
    TS(0, 8, tid == 0);
    {
        const int c = wg, lt = tid & 127;
        const uint8_t* cb = smem + CV_BASE + c * CV_CH_BYTES;
        const uint32_t dw = (c & 2) ? dD.y : dD.x;
        const float Dv = (c & 1) ? bf_hi(dw) : bf_lo(dw);
#pragma unroll
        for (int it = 0; it < 2; it++) {
            const int p = lt + 128 * it;
            const int s0 = 8 * p;
            const float4* p0 = reinterpret_cast<const float4*>(cb + CV_XT_BYTES + CV_WT_BYTES + p * 48);
            const float4* p1 = reinterpret_cast<const float4*>(cb + CV_XT_BYTES + CV_WT_BYTES + CV_P_BYTES + p * 48);
            const uint4 kv = *reinterpret_cast<const uint4*>(cb + ((p & 1) * CV_R + 127 - (p >> 1)) * 16);
            const uint4 xv = *reinterpret_cast<const uint4*>(smem + CV_XS_OFF + c * CV_XS_PITCH + p * 16);
            const uint4 sa_ = *reinterpret_cast<const uint4*>(smem + CV_ST_OFF + s0 * 4), sb_ = *reinterpret_cast<const uint4*>(smem + CV_ST_OFF + s0 * 4 + 16);
            const uint32_t sw_[8] = {sa_.x, sa_.y, sa_.z, sa_.w, sb_.x, sb_.y, sb_.z, sb_.w};
            const float4 a0 = p0[0], a1 = p0[1], b0 = p1[0], b1 = p1[1];
            float y[8] = {a0.x + b0.x, a0.y + b0.y, a0.z + b0.z, a0.w + b0.w, a1.x + b1.x, a1.y + b1.y, a1.z + b1.z, a1.w + b1.w};
            const uint32_t kw[4] = {kv.x, kv.y, kv.z, kv.w};
            const uint32_t xw[4] = {xv.x, xv.y, xv.z, xv.w};
            uint32_t ow[4];
#pragma unroll
            for (int j = 0; j < 4; j++) {
                float e0 = bf_lo(kw[j]) * Dv, e1 = bf_hi(kw[j]) * Dv;
                bf16r2(e0, e1);
                bf16r2(y[2 * j], y[2 * j + 1]);
                const uint32_t zp = pack_bf16(y[2 * j] + e0, y[2 * j + 1] + e1);
                float q0 = bf_lo(xw[j]) - bf_lo(sw_[2 * j]), q1 = bf_hi(xw[j]) - bf_lo(sw_[2 * j + 1]);
                bf16r2(q0, q1);
                const uint32_t qp = pack_bf16(__fdividef(q0, bf_hi(sw_[2 * j])), __fdividef(q1, bf_hi(sw_[2 * j + 1])));
                const bf162 qz = __hmul2_rn(*reinterpret_cast<const bf162*>(&qp), *reinterpret_cast<const bf162*>(&zp));
                const bf162 hv = __hadd2_rn(*reinterpret_cast<const bf162*>(&xw[j]), qz);
                ow[j] = *reinterpret_cast<const uint32_t*>(&hv);
            }
            TS(0, 13, tid == 0 && it == 0);
            asm volatile("st.global.v4.u32 [%0], {%1,%2,%3,%4};" ::"l"(g_hb + (size_t)(p >> 1) * (D_ * 16) + (d0 + c) * 16 + ((p & 1) ^ rank) * 8),
                         "r"(ow[0]), "r"(ow[1]), "r"(ow[2]), "r"(ow[3]) : "memory");
            TS(0, 14, tid == 0 && it == 0);
        }
    }
    TS(0, 12, tid == 0);
    asm volatile("bar.sync %0, 128;" ::"r"(6 + wg) : "memory");
    if ((tid & 127) == 96) {
        __threadfence();
        atomicAdd(&g_c1, 1u);
    }
    fence_proxy_async();
    __syncthreads();
    TS(0, 9, tid == 0);

    if (wg >= 2) {
        asm volatile("setmaxnreg.dec.sync.aligned.u32 24;");
        if (warp == 12 || warp == 13) {
            for (int T = 0; T < 4; T++) {
                asm volatile("bar.sync %0, 160;" ::"r"(warp - 1) : "memory");
                if (lane == 0) {
                    __threadfence();
                    atomicAdd(&g_c2[(mt1 * 2 + (ns >> 2)) * 4 + T], 1u);
                }
                __syncwarp();
            }
        }
        if (tid == 256) {
            for (int i = 0; i < 3; i++) {
                const uint32_t e = barEmpty + 8 * (PRE + i);
                asm volatile("mbarrier.arrive.shared::cta.b64 _, [%0], 2;" ::"r"(e) : "memory");
                asm volatile("mbarrier.arrive.shared::cluster.b64 _, [%0], 2;" ::"r"(mapa(e, rank ^ 1)) : "memory");
            }
            wait_counter(&g_c1, 512u);
            fence_proxy_async_global();
            TS(1, 11, true);
            for (int i = 0; i < 8; i++) {
                mbar_expect_tx(barA + 8 * i, 16384);
                asm volatile("cp.async.bulk.shared::cluster.global.mbarrier::complete_tx::bytes [%0], [%1], %2, [%3];"
                             ::"r"(sb + (A_SLOT0 + i) * SLOT), "l"(g_hb + (size_t)(mt1 * 8 + i) * (D_ * 16)), "r"(16384), "r"(barA + 8 * i) : "memory");
            }
            for (int T = 0; T < 2; T++) wait_counter(&g_c2[(2 * mt2 + rank) * 4 + T], 8u);
            fence_proxy_async_global();
            mbar_wait(barG1, 0);
            for (int j = 0; j < 14; j++) {
                const int st = g2_slotA(j), f = g2_fillA(j);
                if (j == 8 || j == 12) {
                    wait_counter(&g_c2[(2 * mt2 + rank) * 4 + (j >> 2)], 8u);
                    fence_proxy_async_global();
                }
                if (j < NA) mbar_wait(barEmpty + 8 * st, (f - (st < PRE ? 1 : 0)) & 1);
                else mbar_wait(barAE + 8 * (j % NA), (j / NA - 1) & 1);
                mbar_expect_tx(barFull + 8 * st, SLOT);
                asm volatile("cp.async.bulk.shared::cluster.global.mbarrier::complete_tx::bytes [%0], [%1], %2, [%3];"
                             ::"r"(sb + st * SLOT), "l"(reinterpret_cast<const uint8_t*>(g_hh) + ((size_t)mt2 * 28 + rank * 14 + j) * 16384), "r"(16384), "r"(barFull + 8 * st) : "memory");
            }
        } else if (tid == 288) {
            const CUtensorMap* mw = rank ? &map_u : &map_g;
            for (int it = PRE; it < 32; it++) {
                const int st = it % NSLOT, f = it / NSLOT;
                mbar_wait(barEmpty + 8 * st, (f - (st < PRE ? 1 : 0)) & 1);
                if (it < 24) {
                    mbar_expect_tx(barFull + 8 * st, SLOT);
                    tma_load_2d_mc(sb + st * SLOT + rank * 8192, mw, barFull + 8 * st, f0 + 64 * (it >> 3), 64 * (it & 7), (uint16_t)3);
                } else {
                    mbar_expect_tx(barFull + 8 * st, SLOT / 2);
                    tma_load_2d_mc(sb + st * SLOT + rank * 4096, rank ? &map_u32 : &map_g32, barFull + 8 * st, f0 + 192, 64 * (it & 7), (uint16_t)3);
                }
            }
            mbar_arrive(barG1);
            const int c0 = nt * 128, k0 = rank * 896;
            for (int j = 0; j < 14; j++) {
                const int st = g2_slotB(j), f = g2_fillB(j);
                mbar_wait(barEmpty + 8 * st, (f - (st < PRE ? 1 : 0)) & 1);
                mbar_expect_tx(barFull + 8 * st, SLOT);
                if (j < 12) {
                    const int kr = k0 + 224 * (j & 3) + 64 * (j >> 2);
                    tma_load_2d(sb + st * SLOT, &map_d, barFull + 8 * st, c0, kr);
                    tma_load_2d(sb + st * SLOT + 8192, &map_d, barFull + 8 * st, c0 + 64, kr);
                } else {
                    const int kr = k0 + 448 * (j - 12) + 192;
                    tma_load_2d(sb + st * SLOT, &map_d32, barFull + 8 * st, c0, kr);
                    tma_load_2d(sb + st * SLOT + 4096, &map_d32, barFull + 8 * st, c0, kr + 224);
                    tma_load_2d(sb + st * SLOT + 8192, &map_d32, barFull + 8 * st, c0 + 64, kr);
                    tma_load_2d(sb + st * SLOT + 12288, &map_d32, barFull + 8 * st, c0 + 64, kr + 224);
                }
            }
        }
    } else {
        asm volatile("setmaxnreg.inc.sync.aligned.u32 232;");
        const int row1 = mt1 * 128;
        {
            uint32_t a[32][4];
            {
                const uint32_t abase = sb + (A_SLOT0 + warp) * SLOT + ((lane & 7) + 8 * (lane >> 4)) * 32 + (((lane >> 3) ^ (lane >> 2)) & 1) * 16;
                mbar_wait(barA + 8 * warp, 0);
                TS(1, 12, tid == 0);
#pragma unroll
                for (int kk = 0; kk < 32; kk++) {
                    asm volatile("ldmatrix.sync.aligned.m8n8.x4.trans.shared.b16 {%0,%1,%2,%3}, [%4];"
                                 : "=r"(a[kk][0]), "=r"(a[kk][1]), "=r"(a[kk][2]), "=r"(a[kk][3])
                                 : "r"(abase + kk * 512) : "memory");
                }
            }
            TS(1, 14, tid == 0);
            float inv0, inv1;
            {
                float rs[4] = {0.f, 0.f, 0.f, 0.f};
                const uint64_t dones = make_desc(sb + ONES_OFF, 128, 128, 0);
                wgmma_fence();
#pragma unroll
                for (int kk = 0; kk < 32; kk++) wgmma_rs_n8<0>(rs, a[kk][0], a[kk][1], a[kk][2], a[kk][3], (uint32_t)dones, (uint32_t)(dones >> 32));
                wgmma_commit();
                float ga = 0.f, gb = 0.f, gc = 0.f, gd = 0.f;
#pragma unroll
                for (int kk = 0; kk < 32; kk++) {
                    float l, h;
                    l = bf_lo(a[kk][0]); h = bf_hi(a[kk][0]); ga += l * l; gc += h * h;
                    l = bf_lo(a[kk][2]); h = bf_hi(a[kk][2]); ga += l * l; gc += h * h;
                    l = bf_lo(a[kk][1]); h = bf_hi(a[kk][1]); gb += l * l; gd += h * h;
                    l = bf_lo(a[kk][3]); h = bf_hi(a[kk][3]); gb += l * l; gd += h * h;
                }
                ga += gc; gb += gd;
                ga += __shfl_xor_sync(0xffffffffu, ga, 1); ga += __shfl_xor_sync(0xffffffffu, ga, 2);
                gb += __shfl_xor_sync(0xffffffffu, gb, 1); gb += __shfl_xor_sync(0xffffffffu, gb, 2);
                wgmma_wait<0>();
                if (lane == 0) {
                    const uint32_t e = barEmpty + 8 * (A_SLOT0 + warp);
                    asm volatile("mbarrier.arrive.shared::cta.b64 _, [%0], 2;" ::"r"(e) : "memory");
                    asm volatile("mbarrier.arrive.shared::cluster.b64 _, [%0], 2;" ::"r"(mapa(e, rank ^ 1)) : "memory");
                }
                const float mean0 = rs[0] * (1.f / 512.f), mean1 = rs[2] * (1.f / 512.f);
                const uint32_t mp = pack_bf16(mean0, mean1);
                const uint32_t m0 = __byte_perm(mp, 0, 0x1010), m1 = __byte_perm(mp, 0, 0x3232);
#pragma unroll
                for (int kk = 0; kk < 32; kk++) {
#pragma unroll
                    for (int r = 0; r < 4; r++) {
                        const uint32_t mm = (r & 1) ? m1 : m0;
                        const bf162 dd = __hsub2_rn(*reinterpret_cast<const bf162*>(&a[kk][r]), *reinterpret_cast<const bf162*>(&mm));
                        a[kk][r] = *reinterpret_cast<const uint32_t*>(&dd);
                    }
                }
                const float v0 = fmaxf(ga * (1.f / 512.f) - mean0 * mean0, 0.f), v1 = fmaxf(gb * (1.f / 512.f) - mean1 * mean1, 0.f);
                inv0 = __fdividef(1.f, bf16r(sqrtf(bf16r(bf16r(v0) + 1e-5f))));
                inv1 = __fdividef(1.f, bf16r(sqrtf(bf16r(bf16r(v1) + 1e-5f))));
            }
            TS(1, 2, tid == 0);
            if (wg == 1) asm volatile("bar.sync 5, 256;" ::: "memory");
#pragma unroll 1
            for (int T = 0; T < 3; T++) gemm1_pass<true>(T, a, inv0, inv1, sb, rank ^ 1, row1, ns, tid, wg);
            gemm1_pass<false>(3, a, inv0, inv1, sb, rank ^ 1, row1, ns, tid, wg);
        }
        TS(2, 0, tid == 0);

        {
        uint32_t sb_, tid_;
        asm volatile("mov.u32 %0, %1;" : "=r"(sb_) : "r"(sb) : "memory");
        asm volatile("mov.u32 %0, %%tid.x;" : "=r"(tid_) :: "memory");
        const uint32_t sb = sb_;
        const int tid = (int)tid_, warp = tid >> 5, lane = tid & 31;
        const uint32_t barFull = sb + BAR_OFF, barEmpty = barFull + 8 * NSLOT, barA = barEmpty + 8 * NSLOT;
        const uint32_t barX = barA + 64 + 16, barAE = barX + 24, barRdy = barAE + 56;
        const int c0 = nt * 128, row2 = mt2 * 128;
        float acc[64];
#pragma unroll
        for (int i = 0; i < 64; i++) acc[i] = 0.f;
        {
            uint32_t a[2][4][4];
            const uint64_t d0_ = make_desc(sb, 8192, 1024, 1);
            const uint32_t dlo0 = (uint32_t)d0_, dhi = (uint32_t)(d0_ >> 32);
            const uint32_t abase = sb + warp * 2048 + lane * 16;
#pragma unroll
            for (int j = 0; j < 14; j++) {
                const int jj = j & 1;
                const int sa = g2_slotA(j), sbk = g2_slotB(j);
                mbar_wait(barFull + 8 * sa, g2_fillA(j) & 1);
                if (j >= 2) {
                    wgmma_wait<1>();
                    if (j < 8 && (tid & 127) == 0) asm volatile("mbarrier.arrive.shared::cta.b64 _, [%0], 2;" ::"r"(barEmpty + 8 * g2_slotB(j - 2)) : "memory");
                    if (j == 9 && (tid & 127) == 0) mbar_arrive_cluster(mapa(barRdy, rank ^ 1));
                }
#pragma unroll
                for (int kk = 0; kk < 4; kk++)
                    asm volatile("ld.shared.v4.u32 {%0,%1,%2,%3}, [%4];" : "=r"(a[jj][kk][0]), "=r"(a[jj][kk][1]), "=r"(a[jj][kk][2]), "=r"(a[jj][kk][3])
                                 : "r"(abase + sa * SLOT + kk * 512) : "memory");
                mbar_wait(barFull + 8 * sbk, g2_fillB(j) & 1);
                if ((j & 1) == 0) TS(2, 5 + (j >> 1), tid == 128);
                wgmma_fence();
                const uint32_t dlo = dlo0 + sbk * (SLOT / 16);
                wgmma_rst_n128<0>(acc, a[jj][0], dlo, dhi); wgmma_rst_n128<128>(acc, a[jj][1], dlo, dhi);
                wgmma_rst_n128<256>(acc, a[jj][2], dlo, dhi); wgmma_rst_n128<384>(acc, a[jj][3], dlo, dhi);
                wgmma_commit();
                if (j < 14 - NA) {
                    __syncwarp();
                    if (lane == 0) asm volatile("mbarrier.arrive.shared::cta.b64 _, [%0];" ::"r"(barAE + 8 * (j % NA)) : "memory");
                }
            }
        }
        uint4 hv[4];
        {
            const uint4* hsrc = reinterpret_cast<const uint4*>(g_hb + (size_t)(mt2 * 8 + warp) * (D_ * 16) + (c0 + 64 * rank) * 16);
#pragma unroll
            for (int i = 0; i < 4; i++) hv[i] = __ldcg(hsrc + lane + 32 * i);
        }
        wgmma_wait<0>();
        TS(2, 1 + wg, (tid & 127) == 0);
        {
            const uint32_t dst = mapa(sb + X_OFF + tid * 16, rank ^ 1);
            const uint32_t dbar = mapa(barX, rank ^ 1);
            mbar_wait(barRdy, 0);
#pragma unroll
            for (int j = 0; j < 8; j++) {
                uint32_t v[4];
#pragma unroll
                for (int e = 0; e < 4; e++) v[e] = __float_as_uint(rank == 0 ? acc[32 + 4 * j + e] : acc[4 * j + e]);
                st_async_v4(dst + j * 4096, v, dbar);
            }
        }
        asm volatile("bar.sync 4, 256;" ::: "memory");
        const uint32_t stg = sb + warp * 2048;
#pragma unroll
        for (int i = 0; i < 4; i++)
            asm volatile("st.shared.v4.u32 [%0], {%1,%2,%3,%4};" ::"r"(stg + (lane + 32 * i) * 16), "r"(hv[i].x), "r"(hv[i].y), "r"(hv[i].z), "r"(hv[i].w) : "memory");
        __syncwarp();
        uint32_t hf_[8][2];
#pragma unroll
        for (int j = 0; j < 8; j += 2) {
            asm volatile("ldmatrix.sync.aligned.m8n8.x4.trans.shared.b16 {%0,%1,%2,%3}, [%4];"
                         : "=r"(hf_[j][0]), "=r"(hf_[j][1]), "=r"(hf_[j + 1][0]), "=r"(hf_[j + 1][1])
                         : "r"(stg + (8 * j + (lane & 7) + 8 * (lane >> 4)) * 32 + (((lane >> 3) ^ (lane >> 2)) & 1) * 16) : "memory");
        }
        __syncwarp();
        mbar_wait(barX, 0);
        uint32_t po[8][2];
#pragma unroll
        for (int j = 0; j < 8; j++) {
            float4 v;
            asm volatile("ld.shared.v4.f32 {%0,%1,%2,%3}, [%4];" : "=f"(v.x), "=f"(v.y), "=f"(v.z), "=f"(v.w) : "r"(sb + X_OFF + tid * 16 + j * 4096));
            float o0, o1, o2, o3;
            if (rank == 0) { o0 = acc[4 * j] + v.x; o1 = acc[4 * j + 1] + v.y; o2 = acc[4 * j + 2] + v.z; o3 = acc[4 * j + 3] + v.w; }
            else { o0 = acc[32 + 4 * j] + v.x; o1 = acc[33 + 4 * j] + v.y; o2 = acc[34 + 4 * j] + v.z; o3 = acc[35 + 4 * j] + v.w; }
            bf16r2(o0, o1); bf16r2(o2, o3);
            po[j][0] = pack_bf16(bf_lo(hf_[j][0]) + o0, bf_hi(hf_[j][0]) + o1);
            po[j][1] = pack_bf16(bf_lo(hf_[j][1]) + o2, bf_hi(hf_[j][1]) + o3);
        }
        const int mi = lane >> 3, rr = lane & 7;
#pragma unroll
        for (int j = 0; j < 8; j += 2) {
            const int row = rr + 8 * (mi & 1);
            const int chunk = j + (mi >> 1);
            stmatrix_x4(stg + row * 128 + ((chunk ^ (row & 7)) * 16), po[j][0], po[j][1], po[j + 1][0], po[j + 1][1]);
        }
        __syncwarp();
        const size_t obase = (size_t)(row2 + 16 * warp) * D_ + c0 + 64 * rank;
#pragma unroll
        for (int i = 0; i < 4; i++) {
            const int row = 4 * i + (lane >> 3), chunk = lane & 7;
            uint4 v;
            asm volatile("ld.shared.v4.u32 {%0,%1,%2,%3}, [%4];" : "=r"(v.x), "=r"(v.y), "=r"(v.z), "=r"(v.w) : "r"(stg + row * 128 + ((chunk ^ (row & 7)) * 16)));
            *reinterpret_cast<uint4*>(out + obase + (size_t)row * D_ + chunk * 8) = v;
        }
        TS(2, 3 + wg, (tid & 127) == 0);
        if (warp == 0) {
            unsigned int last = 0;
            if (lane == 0) last = (atomicAdd(&g_c3, 1u) == 127u);
            last = __shfl_sync(0xffffffffu, last, 0);
            if (last) {
                reinterpret_cast<uint4*>(g_c2)[lane] = make_uint4(0u, 0u, 0u, 0u);
                if (lane == 0) { g_c1 = 0u; g_c3 = 0u; }
            }
        }
        }
    }
}

typedef CUresult (*PFN_encodeTiled)(CUtensorMap*, CUtensorMapDataType, cuuint32_t, void*, const cuuint64_t*, const cuuint64_t*,
                                    const cuuint32_t*, const cuuint32_t*, CUtensorMapInterleave, CUtensorMapSwizzle,
                                    CUtensorMapL2promotion, CUtensorMapFloatOOBfill);

static void make_map(PFN_encodeTiled enc, CUtensorMap* m, const void* ptr, uint64_t inner, uint64_t outer, uint32_t box_inner, uint32_t box_outer,
                     CUtensorMapSwizzle swz = CU_TENSOR_MAP_SWIZZLE_128B) {
    cuuint64_t dims[2] = {inner, outer};
    cuuint64_t strides[1] = {inner * 2};
    cuuint32_t box[2] = {box_inner, box_outer};
    cuuint32_t es[2] = {1, 1};
    enc(m, CU_TENSOR_MAP_DATA_TYPE_BFLOAT16, 2, const_cast<void*>(ptr), dims, strides, box, es, CU_TENSOR_MAP_INTERLEAVE_NONE,
        swz, CU_TENSOR_MAP_L2_PROMOTION_L2_256B, CU_TENSOR_MAP_FLOAT_OOB_FILL_NONE);
}

extern "C" void kernel_launch(void* const* d_in, const int* in_sizes, int n_in, void* d_out, int out_size) {
    const bf16* A_q = (const bf16*)d_in[0];
    const bf16* A_k = (const bf16*)d_in[1];
    const bf16* A_v = (const bf16*)d_in[2];
    const bf16* A_shift = (const bf16*)d_in[3];
    const bf16* A_ssmk = (const bf16*)d_in[4];
    const bf16* A_ssmD = (const bf16*)d_in[5];
    const bf16* w_gate = (const bf16*)d_in[7];
    const bf16* w_up = (const bf16*)d_in[8];
    const bf16* w_down = (const bf16*)d_in[9];

    static bool init = false;
    static CUtensorMap map_g, map_u, map_g32, map_u32, map_d, map_d32, map_k, map_kh, map_v, map_x;
    static const void* cached[6] = {nullptr, nullptr, nullptr, nullptr, nullptr, nullptr};
    if (!init || cached[0] != w_gate || cached[1] != w_up || cached[2] != w_down || cached[3] != A_q || cached[4] != A_k || cached[5] != A_v) {
        void* fn = nullptr;
        cudaDriverEntryPointQueryResult qres;
        cudaGetDriverEntryPoint("cuTensorMapEncodeTiled", &fn, cudaEnableDefault, &qres);
        PFN_encodeTiled enc = (PFN_encodeTiled)fn;
        make_map(enc, &map_g, w_gate, F_, D_, 64, 64);
        make_map(enc, &map_u, w_up, F_, D_, 64, 64);
        make_map(enc, &map_g32, w_gate, F_, D_, 32, 64, CU_TENSOR_MAP_SWIZZLE_64B);
        make_map(enc, &map_u32, w_up, F_, D_, 32, 64, CU_TENSOR_MAP_SWIZZLE_64B);
        make_map(enc, &map_d, w_down, D_, F_, 64, 64);
        make_map(enc, &map_d32, w_down, D_, F_, 64, 32);
        make_map(enc, &map_k, A_k, D_, S_, 8, 256, CU_TENSOR_MAP_SWIZZLE_NONE);
        make_map(enc, &map_kh, A_k, D_, S_, 8, 8, CU_TENSOR_MAP_SWIZZLE_NONE);
        make_map(enc, &map_v, A_v, D_, S_, 8, 256, CU_TENSOR_MAP_SWIZZLE_NONE);
        make_map(enc, &map_x, A_q, D_, S_, 8, 256, CU_TENSOR_MAP_SWIZZLE_NONE);
        cudaFuncSetAttribute(mega_kernel, cudaFuncAttributeMaxDynamicSharedMemorySize, SMEM_BYTES);
        cached[0] = w_gate; cached[1] = w_up; cached[2] = w_down; cached[3] = A_q; cached[4] = A_k; cached[5] = A_v;
        init = true;
    }
    mega_kernel<<<128, 512, SMEM_BYTES, cudaStreamPerThread>>>(A_q, A_k, A_v, A_shift, A_ssmk, A_ssmD, w_gate, w_up, w_down, (bf16*)d_out,
                                                               map_g, map_u, map_g32, map_u32, map_d, map_d32, map_k, map_kh, map_v, map_x);
}
```

```cpp
#include <cuda_runtime.h>
#include <cuda_bf16.h>
#include <cuda.h>
#include <stdint.h>

typedef __nv_bfloat16 bf16;
typedef __nv_bfloat162 bf162;

constexpr int S_ = 2048, D_ = 512, F_ = 1792;

__device__ __align__(1024) bf16 g_hb[S_ * D_];
__device__ __align__(1024) bf16 g_hh[S_ * F_];
__device__ __align__(128) uint32_t g_stats[S_];
__device__ unsigned int g_bar;
__device__ unsigned int g_c1;
__device__ __align__(16) unsigned int g_c2[128];
__device__ unsigned int g_c3;

#define TS_INIT()
#define TS_DUMP()
#define TS(k, i, cond)

__device__ __forceinline__ uint32_t smem_u32(const void* p) { return (uint32_t)__cvta_generic_to_shared(p); }

__device__ __forceinline__ void mbar_init(uint32_t bar, uint32_t count) {
    asm volatile("mbarrier.init.shared::cta.b64 [%0], %1;" ::"r"(bar), "r"(count) : "memory");
}
__device__ __forceinline__ void mbar_expect_tx(uint32_t bar, uint32_t bytes) {
    asm volatile("mbarrier.arrive.expect_tx.shared::cta.b64 _, [%0], %1;" ::"r"(bar), "r"(bytes) : "memory");
}
__device__ __forceinline__ void mbar_arrive(uint32_t bar) {
    asm volatile("mbarrier.arrive.shared::cta.b64 _, [%0];" ::"r"(bar) : "memory");
}
__device__ __forceinline__ uint32_t mapa(uint32_t addr, uint32_t rank) {
    uint32_t r;
    asm volatile("mapa.shared::cluster.u32 %0, %1, %2;" : "=r"(r) : "r"(addr), "r"(rank));
    return r;
}
__device__ __forceinline__ void mbar_arrive_cluster(uint32_t cluster_addr) {
    asm volatile("mbarrier.arrive.shared::cluster.b64 _, [%0];" ::"r"(cluster_addr) : "memory");
}
__device__ __forceinline__ void mbar_wait(uint32_t bar, uint32_t parity) {
    asm volatile(
        "{\n.reg .pred p;\n.reg .u32 c;\n"
        "mov.u32 c, 0;\n"
        "WAIT_%=:\n"
        "mbarrier.try_wait.parity.shared::cta.b64 p, [%0], %1;\n"
        "@p bra DONE_%=;\n"
        "add.u32 c, c, 1;\n"
        "setp.lt.u32 p, c, 4194304;\n"
        "@p bra WAIT_%=;\n"
        "DONE_%=:\n}\n"
        ::"r"(bar), "r"(parity) : "memory");
}
__device__ __forceinline__ void wait_counter(const unsigned int* p, unsigned int target) {
    unsigned int v, it = 0;
    do {
        asm volatile("ld.acquire.gpu.global.u32 %0, [%1];" : "=r"(v) : "l"(p) : "memory");
        if (++it > (1u << 24)) break;
    } while (v < target);
}
__device__ __forceinline__ void cluster_arrive() { asm volatile("barrier.cluster.arrive.release.aligned;" ::: "memory"); }
__device__ __forceinline__ void cluster_wait() { asm volatile("barrier.cluster.wait.acquire.aligned;" ::: "memory"); }
__device__ __forceinline__ void fence_proxy_async() { asm volatile("fence.proxy.async.shared::cta;" ::: "memory"); }
__device__ __forceinline__ void fence_proxy_async_global() { asm volatile("fence.proxy.async.global;" ::: "memory"); }
__device__ __forceinline__ void wgmma_fence() { asm volatile("wgmma.fence.sync.aligned;" ::: "memory"); }
__device__ __forceinline__ void wgmma_commit() { asm volatile("wgmma.commit_group.sync.aligned;" ::: "memory"); }
template <int N> __device__ __forceinline__ void wgmma_wait() { asm volatile("wgmma.wait_group.sync.aligned %0;" ::"n"(N) : "memory"); }

__device__ __forceinline__ void tma_load_2d(uint32_t dst, const CUtensorMap* map, uint32_t bar, int c0, int c1) {
    asm volatile(
        "cp.async.bulk.tensor.2d.shared::cluster.global.mbarrier::complete_tx::bytes [%0], [%1, {%3, %4}], [%2];"
        ::"r"(dst), "l"(map), "r"(bar), "r"(c0), "r"(c1) : "memory");
}
__device__ __forceinline__ void tma_load_2d_mc(uint32_t dst, const CUtensorMap* map, uint32_t bar, int c0, int c1, uint16_t mask) {
    asm volatile(
        "cp.async.bulk.tensor.2d.shared::cluster.global.mbarrier::complete_tx::bytes.multicast::cluster [%0], [%1, {%3, %4}], [%2], %5;"
        ::"r"(dst), "l"(map), "r"(bar), "r"(c0), "r"(c1), "h"(mask) : "memory");
}

__device__ __forceinline__ uint64_t make_desc(uint32_t addr, uint32_t lbo_bytes, uint32_t sbo_bytes, uint32_t swz) {
    uint64_t d = 0;
    d |= (uint64_t)((addr & 0x3FFFF) >> 4);
    d |= (uint64_t)((lbo_bytes & 0x3FFFF) >> 4) << 16;
    d |= (uint64_t)((sbo_bytes & 0x3FFFF) >> 4) << 32;
    d |= (uint64_t)swz << 62;
    return d;
}

__device__ __forceinline__ float bf16r(float x) { return __bfloat162float(__float2bfloat16_rn(x)); }
__device__ __forceinline__ uint32_t pack_bf16(float lo, float hi) {
    bf162 v = __floats2bfloat162_rn(lo, hi);
    return *reinterpret_cast<uint32_t*>(&v);
}
__device__ __forceinline__ float bf_lo(uint32_t u) { return __uint_as_float(u << 16); }
__device__ __forceinline__ float bf_hi(uint32_t u) { return __uint_as_float(u & 0xffff0000u); }
__device__ __forceinline__ void bf16r2(float& a, float& b) {
    const uint32_t p = pack_bf16(a, b);
    a = bf_lo(p); b = bf_hi(p);
}

__device__ __forceinline__ void stmatrix_x4(uint32_t addr, uint32_t r0, uint32_t r1, uint32_t r2, uint32_t r3) {
    asm volatile("stmatrix.sync.aligned.m8n8.x4.shared.b16 [%0], {%1,%2,%3,%4};" ::"r"(addr), "r"(r0), "r"(r1), "r"(r2), "r"(r3) : "memory");
}

template <int OFF>
__device__ __forceinline__ void wgmma_rs_n128(float* d, uint32_t a0, uint32_t a1, uint32_t a2, uint32_t a3, uint32_t dlo, uint32_t dhi) {
    asm volatile(
        "{\n.reg .b64 dsc;\n.reg .b32 lo;\nadd.s32 lo, %68, %70;\nmov.b64 dsc, {lo, %69};\n"
        "wgmma.mma_async.sync.aligned.m64n128k16.f32.bf16.bf16 "
        "{%0,%1,%2,%3,%4,%5,%6,%7,%8,%9,%10,%11,%12,%13,%14,%15,%16,%17,%18,%19,%20,%21,%22,%23,%24,%25,%26,%27,%28,%29,%30,%31,%32,%33,%34,%35,%36,%37,%38,%39,%40,%41,%42,%43,%44,%45,%46,%47,%48,%49,%50,%51,%52,%53,%54,%55,%56,%57,%58,%59,%60,%61,%62,%63}, {%64,%65,%66,%67}, dsc, 1, 1, 1, 0;\n}\n"
        : "+f"(d[0]), "+f"(d[1]), "+f"(d[2]), "+f"(d[3]), "+f"(d[4]), "+f"(d[5]), "+f"(d[6]), "+f"(d[7]), "+f"(d[8]), "+f"(d[9]), "+f"(d[10]), "+f"(d[11]), "+f"(d[12]), "+f"(d[13]), "+f"(d[14]), "+f"(d[15]), "+f"(d[16]), "+f"(d[17]), "+f"(d[18]), "+f"(d[19]), "+f"(d[20]), "+f"(d[21]), "+f"(d[22]), "+f"(d[23]), "+f"(d[24]), "+f"(d[25]), "+f"(d[26]), "+f"(d[27]), "+f"(d[28]), "+f"(d[29]), "+f"(d[30]), "+f"(d[31]), "+f"(d[32]), "+f"(d[33]), "+f"(d[34]), "+f"(d[35]), "+f"(d[36]), "+f"(d[37]), "+f"(d[38]), "+f"(d[39]), "+f"(d[40]), "+f"(d[41]), "+f"(d[42]), "+f"(d[43]), "+f"(d[44]), "+f"(d[45]), "+f"(d[46]), "+f"(d[47]), "+f"(d[48]), "+f"(d[49]), "+f"(d[50]), "+f"(d[51]), "+f"(d[52]), "+f"(d[53]), "+f"(d[54]), "+f"(d[55]), "+f"(d[56]), "+f"(d[57]), "+f"(d[58]), "+f"(d[59]), "+f"(d[60]), "+f"(d[61]), "+f"(d[62]), "+f"(d[63])
        : "r"(a0), "r"(a1), "r"(a2), "r"(a3), "r"(dlo), "r"(dhi), "n"(OFF));
}
template <int OFF>
__device__ __forceinline__ void wgmma_rs_n96(float* d, uint32_t a0, uint32_t a1, uint32_t a2, uint32_t a3, uint32_t dlo, uint32_t dhi) {
    asm volatile(
        "{\n.reg .b64 dsc;\n.reg .b32 lo;\nadd.s32 lo, %52, %54;\nmov.b64 dsc, {lo, %53};\n"
        "wgmma.mma_async.sync.aligned.m64n96k16.f32.bf16.bf16 "
        "{%0,%1,%2,%3,%4,%5,%6,%7,%8,%9,%10,%11,%12,%13,%14,%15,%16,%17,%18,%19,%20,%21,%22,%23,%24,%25,%26,%27,%28,%29,%30,%31,%32,%33,%34,%35,%36,%37,%38,%39,%40,%41,%42,%43,%44,%45,%46,%47}, {%48,%49,%50,%51}, dsc, 1, 1, 1, 0;\n}\n"
        : "+f"(d[0]), "+f"(d[1]), "+f"(d[2]), "+f"(d[3]), "+f"(d[4]), "+f"(d[5]), "+f"(d[6]), "+f"(d[7]), "+f"(d[8]), "+f"(d[9]), "+f"(d[10]), "+f"(d[11]), "+f"(d[12]), "+f"(d[13]), "+f"(d[14]), "+f"(d[15]), "+f"(d[16]), "+f"(d[17]), "+f"(d[18]), "+f"(d[19]), "+f"(d[20]), "+f"(d[21]), "+f"(d[22]), "+f"(d[23]), "+f"(d[24]), "+f"(d[25]), "+f"(d[26]), "+f"(d[27]), "+f"(d[28]), "+f"(d[29]), "+f"(d[30]), "+f"(d[31]), "+f"(d[32]), "+f"(d[33]), "+f"(d[34]), "+f"(d[35]), "+f"(d[36]), "+f"(d[37]), "+f"(d[38]), "+f"(d[39]), "+f"(d[40]), "+f"(d[41]), "+f"(d[42]), "+f"(d[43]), "+f"(d[44]), "+f"(d[45]), "+f"(d[46]), "+f"(d[47])
        : "r"(a0), "r"(a1), "r"(a2), "r"(a3), "r"(dlo), "r"(dhi), "n"(OFF));
}
template <int OFF>
__device__ __forceinline__ void wgmma_rs_n64(float* d, uint32_t a0, uint32_t a1, uint32_t a2, uint32_t a3, uint32_t dlo, uint32_t dhi) {
    asm volatile(
        "{\n.reg .b64 dsc;\n.reg .b32 lo;\nadd.s32 lo, %36, %38;\nmov.b64 dsc, {lo, %37};\n"
        "wgmma.mma_async.sync.aligned.m64n64k16.f32.bf16.bf16 "
        "{%0,%1,%2,%3,%4,%5,%6,%7,%8,%9,%10,%11,%12,%13,%14,%15,%16,%17,%18,%19,%20,%21,%22,%23,%24,%25,%26,%27,%28,%29,%30,%31}, {%32,%33,%34,%35}, dsc, 1, 1, 1, 0;\n}\n"
        : "+f"(d[0]), "+f"(d[1]), "+f"(d[2]), "+f"(d[3]), "+f"(d[4]), "+f"(d[5]), "+f"(d[6]), "+f"(d[7]), "+f"(d[8]), "+f"(d[9]), "+f"(d[10]), "+f"(d[11]), "+f"(d[12]), "+f"(d[13]), "+f"(d[14]), "+f"(d[15]), "+f"(d[16]), "+f"(d[17]), "+f"(d[18]), "+f"(d[19]), "+f"(d[20]), "+f"(d[21]), "+f"(d[22]), "+f"(d[23]), "+f"(d[24]), "+f"(d[25]), "+f"(d[26]), "+f"(d[27]), "+f"(d[28]), "+f"(d[29]), "+f"(d[30]), "+f"(d[31])
        : "r"(a0), "r"(a1), "r"(a2), "r"(a3), "r"(dlo), "r"(dhi), "n"(OFF));
}
template <int OFF>
__device__ __forceinline__ void wgmma_rs_n32(float* d, uint32_t a0, uint32_t a1, uint32_t a2, uint32_t a3, uint32_t dlo, uint32_t dhi) {
    asm volatile(
        "{\n.reg .b64 dsc;\n.reg .b32 lo;\nadd.s32 lo, %20, %22;\nmov.b64 dsc, {lo, %21};\n"
        "wgmma.mma_async.sync.aligned.m64n32k16.f32.bf16.bf16 "
        "{%0,%1,%2,%3,%4,%5,%6,%7,%8,%9,%10,%11,%12,%13,%14,%15}, {%16,%17,%18,%19}, dsc, 1, 1, 1, 0;\n}\n"
        : "+f"(d[0]), "+f"(d[1]), "+f"(d[2]), "+f"(d[3]), "+f"(d[4]), "+f"(d[5]), "+f"(d[6]), "+f"(d[7]), "+f"(d[8]), "+f"(d[9]), "+f"(d[10]), "+f"(d[11]), "+f"(d[12]), "+f"(d[13]), "+f"(d[14]), "+f"(d[15])
        : "r"(a0), "r"(a1), "r"(a2), "r"(a3), "r"(dlo), "r"(dhi), "n"(OFF));
}
template <int OFF>
__device__ __forceinline__ void wgmma_rs_n8(float* d, uint32_t a0, uint32_t a1, uint32_t a2, uint32_t a3, uint32_t dlo, uint32_t dhi) {
    asm volatile(
        "{\n.reg .b64 dsc;\n.reg .b32 lo;\nadd.s32 lo, %8, %10;\nmov.b64 dsc, {lo, %9};\n"
        "wgmma.mma_async.sync.aligned.m64n8k16.f32.bf16.bf16 "
        "{%0,%1,%2,%3}, {%4,%5,%6,%7}, dsc, 1, 1, 1, 0;\n}\n"
        : "+f"(d[0]), "+f"(d[1]), "+f"(d[2]), "+f"(d[3])
        : "r"(a0), "r"(a1), "r"(a2), "r"(a3), "r"(dlo), "r"(dhi), "n"(OFF));
}
template <int OFF>
__device__ __forceinline__ void wgmma_rst_n128(float* d, const uint32_t* a, uint32_t dlo, uint32_t dhi) {
    asm volatile(
        "{\n.reg .b64 dsc;\n.reg .b32 lo;\nadd.s32 lo, %68, %70;\nmov.b64 dsc, {lo, %69};\n"
        "wgmma.mma_async.sync.aligned.m64n128k16.f32.bf16.bf16 "
        "{%0,%1,%2,%3,%4,%5,%6,%7,%8,%9,%10,%11,%12,%13,%14,%15,%16,%17,%18,%19,%20,%21,%22,%23,%24,%25,%26,%27,%28,%29,%30,%31,%32,%33,%34,%35,%36,%37,%38,%39,%40,%41,%42,%43,%44,%45,%46,%47,%48,%49,%50,%51,%52,%53,%54,%55,%56,%57,%58,%59,%60,%61,%62,%63}, {%64,%65,%66,%67}, dsc, 1, 1, 1, 1;\n}\n"
        : "+f"(d[0]), "+f"(d[1]), "+f"(d[2]), "+f"(d[3]), "+f"(d[4]), "+f"(d[5]), "+f"(d[6]), "+f"(d[7]), "+f"(d[8]), "+f"(d[9]), "+f"(d[10]), "+f"(d[11]), "+f"(d[12]), "+f"(d[13]), "+f"(d[14]), "+f"(d[15]), "+f"(d[16]), "+f"(d[17]), "+f"(d[18]), "+f"(d[19]), "+f"(d[20]), "+f"(d[21]), "+f"(d[22]), "+f"(d[23]), "+f"(d[24]), "+f"(d[25]), "+f"(d[26]), "+f"(d[27]), "+f"(d[28]), "+f"(d[29]), "+f"(d[30]), "+f"(d[31]), "+f"(d[32]), "+f"(d[33]), "+f"(d[34]), "+f"(d[35]), "+f"(d[36]), "+f"(d[37]), "+f"(d[38]), "+f"(d[39]), "+f"(d[40]), "+f"(d[41]), "+f"(d[42]), "+f"(d[43]), "+f"(d[44]), "+f"(d[45]), "+f"(d[46]), "+f"(d[47]), "+f"(d[48]), "+f"(d[49]), "+f"(d[50]), "+f"(d[51]), "+f"(d[52]), "+f"(d[53]), "+f"(d[54]), "+f"(d[55]), "+f"(d[56]), "+f"(d[57]), "+f"(d[58]), "+f"(d[59]), "+f"(d[60]), "+f"(d[61]), "+f"(d[62]), "+f"(d[63])
        : "r"(a[0]), "r"(a[1]), "r"(a[2]), "r"(a[3]), "r"(dlo), "r"(dhi), "n"(OFF));
}
template <int OFF>
__device__ __forceinline__ void wgmma_rst_n64(float* d, const uint32_t* a, uint32_t dlo, uint32_t dhi) {
    asm volatile(
        "{\n.reg .b64 dsc;\n.reg .b32 lo;\nadd.s32 lo, %36, %38;\nmov.b64 dsc, {lo, %37};\n"
        "wgmma.mma_async.sync.aligned.m64n64k16.f32.bf16.bf16 "
        "{%0,%1,%2,%3,%4,%5,%6,%7,%8,%9,%10,%11,%12,%13,%14,%15,%16,%17,%18,%19,%20,%21,%22,%23,%24,%25,%26,%27,%28,%29,%30,%31}, {%32,%33,%34,%35}, dsc, 1, 1, 1, 1;\n}\n"
        : "+f"(d[0]), "+f"(d[1]), "+f"(d[2]), "+f"(d[3]), "+f"(d[4]), "+f"(d[5]), "+f"(d[6]), "+f"(d[7]), "+f"(d[8]), "+f"(d[9]), "+f"(d[10]), "+f"(d[11]), "+f"(d[12]), "+f"(d[13]), "+f"(d[14]), "+f"(d[15]), "+f"(d[16]), "+f"(d[17]), "+f"(d[18]), "+f"(d[19]), "+f"(d[20]), "+f"(d[21]), "+f"(d[22]), "+f"(d[23]), "+f"(d[24]), "+f"(d[25]), "+f"(d[26]), "+f"(d[27]), "+f"(d[28]), "+f"(d[29]), "+f"(d[30]), "+f"(d[31])
        : "r"(a[0]), "r"(a[1]), "r"(a[2]), "r"(a[3]), "r"(dlo), "r"(dhi), "n"(OFF));
}

constexpr int NSLOT = 14;
constexpr int SLOT = 16384;
constexpr int X_OFF = 10 * SLOT;
constexpr int BAR_OFF = NSLOT * SLOT;
constexpr int ONES_OFF = BAR_OFF + 512;
constexpr int SMEM_BYTES = BAR_OFF + 800 + 1024;
constexpr int PRE = 3;
constexpr int G1_LAG = 4;
constexpr int A_SLOT0 = 6;
constexpr int CV_BASE = PRE * SLOT;
constexpr int CV_R = 156;
constexpr int CV_XT_BYTES = 2 * CV_R * 16;
constexpr int CV_WT_BYTES = 2064 * 4;
constexpr int CV_P_BYTES = 3072 * 4;
constexpr int CV_CH_BYTES = CV_XT_BYTES + CV_WT_BYTES + 2 * CV_P_BYTES + 80;
static_assert(CV_CH_BYTES % 128 == 16, "channel pitch");
constexpr int CV_XS_OFF = CV_BASE + 4 * CV_CH_BYTES;
constexpr int CV_XS_PITCH = 4096 + 16;
constexpr int CV_ST_OFF = CV_XS_OFF + 4 * CV_XS_PITCH;
static_assert(CV_XS_OFF % 16 == 0 && CV_ST_OFF % 16 == 0 && CV_ST_OFF + 8192 <= BAR_OFF, "conv layout");
constexpr int cv_stage(int c) { return (CV_BASE + c * CV_CH_BYTES + CV_XT_BYTES + CV_WT_BYTES + 1023) / 1024 * 1024; }
constexpr int CV_KS_OFF = cv_stage(0), CV_VS_OFF = cv_stage(1), CV_XI_OFF = cv_stage(2);
static_assert(CV_KS_OFF + 1024 + 16384 <= CV_BASE + CV_CH_BYTES && CV_VS_OFF + 16384 <= CV_BASE + 2 * CV_CH_BYTES && CV_XI_OFF + 16384 <= CV_BASE + 3 * CV_CH_BYTES, "staging");

__device__ __forceinline__ void conv_load(uint32_t (&w)[6], const uint32_t* wp) {
#pragma unroll
    for (int s = 0; s < 2; s++) { w[3 * s] = wp[64 * s - 8]; w[3 * s + 1] = wp[64 * s]; w[3 * s + 2] = wp[64 * s + 8]; }
}
template <int L, int OFF>
__device__ __forceinline__ void conv_mma1(float* acc, uint32_t a2, uint32_t a0, uint32_t a1, uint32_t dlo, uint32_t dhi) {
    if (L == 0) wgmma_rs_n128<OFF>(acc, a0, a1, a2, a0, dlo, dhi);
    else if (L == 1) wgmma_rs_n128<OFF>(acc, a0, a1, a2, a0, dlo, dhi);
    else if (L == 2) wgmma_rs_n96<OFF>(acc, a0, a1, a2, a0, dlo, dhi);
    else if (L == 3) wgmma_rs_n96<OFF>(acc, a0, a1, a2, a0, dlo, dhi);
    else if (L == 4) wgmma_rs_n64<OFF>(acc, a0, a1, a2, a0, dlo, dhi);
    else if (L == 5) wgmma_rs_n64<OFF>(acc, a0, a1, a2, a0, dlo, dhi);
    else if (L == 6) wgmma_rs_n32<OFF>(acc, a0, a1, a2, a0, dlo, dhi);
    else wgmma_rs_n32<OFF>(acc, a0, a1, a2, a0, dlo, dhi);
}
template <int B>
__device__ __forceinline__ void conv_issue(float* acc, const uint32_t (&w)[6], uint32_t dlo, uint32_t dhi) {
    wgmma_fence();
    conv_mma1<(B >> 1), 8 * B + 0>(acc, w[0], w[1], w[2], dlo, dhi);
    conv_mma1<(B >> 1), 8 * B + 4>(acc, w[3], w[4], w[5], dlo, dhi);
    wgmma_commit();
}
template <int B>
__device__ __forceinline__ void conv_pair(float* acc, uint32_t (&q0)[6], uint32_t (&q1)[6], const uint32_t* wp, uint32_t dlo, uint32_t dhi) {
    if (B > 0 && (B & 3) == 0) wgmma_wait<0>();
    conv_issue<B>(acc, q0, dlo, dhi);
    if ((B & 3) != 0) wgmma_wait<1>();
    conv_load(q1, wp + 128 * (B + 1));
    conv_issue<B + 1>(acc, q1, dlo, dhi);
    if (B + 2 < 16) {
        wgmma_wait<1>();
        conv_load(q0, wp + 128 * (B + 2));
    }
}
__device__ __forceinline__ void conv_mma(float* acc, const uint32_t* wp, uint32_t xt_base) {
    uint32_t q0[6], q1[6];
    const uint64_t desc0 = make_desc(xt_base, CV_R * 16, 128, 0);
    const uint32_t dlo = (uint32_t)desc0, dhi = (uint32_t)(desc0 >> 32);
    conv_load(q0, wp);
    conv_pair<0>(acc, q0, q1, wp, dlo, dhi);
    conv_pair<2>(acc, q0, q1, wp, dlo, dhi);
    conv_pair<4>(acc, q0, q1, wp, dlo, dhi);
    conv_pair<6>(acc, q0, q1, wp, dlo, dhi);
    conv_pair<8>(acc, q0, q1, wp, dlo, dhi);
    conv_pair<10>(acc, q0, q1, wp, dlo, dhi);
    conv_pair<12>(acc, q0, q1, wp, dlo, dhi);
    conv_pair<14>(acc, q0, q1, wp, dlo, dhi);
    wgmma_wait<0>();
}
__device__ __forceinline__ float warp_sum(float v) {
#pragma unroll
    for (int o = 16; o > 0; o >>= 1) v += __shfl_xor_sync(0xffffffffu, v, o);
    return v;
}
__device__ __forceinline__ float sigmoid_f(float x) {
    float e, r;
    asm("ex2.approx.ftz.f32 %0, %1;" : "=f"(e) : "f"(x * -1.4426950408889634f));
    asm("rcp.approx.ftz.f32 %0, %1;" : "=f"(r) : "f"(1.f + e));
    return r;
}
__device__ __forceinline__ void st_async_v4(uint32_t addr, const uint32_t (&c)[4], uint32_t bar) {
    asm volatile("st.async.weak.shared::cluster.mbarrier::complete_tx::bytes.v4.b32 [%0], {%1,%2,%3,%4}, [%5];"
                 ::"r"(addr), "r"(c[0]), "r"(c[1]), "r"(c[2]), "r"(c[3]), "r"(bar) : "memory");
}

__device__ __forceinline__ void load_chunk_t(uint32_t addr_rows, int lane, uint32_t (&r)[4]) {
    asm volatile("ldmatrix.sync.aligned.m8n8.x4.trans.shared.b16 {%0,%1,%2,%3}, [%4];"
                 : "=r"(r[0]), "=r"(r[1]), "=r"(r[2]), "=r"(r[3]) : "r"(addr_rows + lane * 16) : "memory");
    const bool b0 = lane & 1, b1 = lane & 2;
    uint32_t x, y;
    x = b0 ? r[0] : r[1]; y = b0 ? r[2] : r[3];
    x = __shfl_xor_sync(0xffffffffu, x, 1); y = __shfl_xor_sync(0xffffffffu, y, 1);
    if (b0) { r[0] = x; r[2] = y; } else { r[1] = x; r[3] = y; }
    x = b1 ? r[0] : r[2]; y = b1 ? r[1] : r[3];
    x = __shfl_xor_sync(0xffffffffu, x, 2); y = __shfl_xor_sync(0xffffffffu, y, 2);
    if (b1) { r[0] = x; r[1] = y; } else { r[2] = x; r[3] = y; }
}

template <bool FULL>
__device__ __forceinline__ void gemm1_pass(int T, const uint32_t (&a)[32][4], float inv0, float inv1, uint32_t sb, uint32_t peer,
                                           int row0, int f0, int tid, int wg) {
    const int warp = tid >> 5, lane = tid & 31;
    const uint32_t barFull = sb + BAR_OFF, barEmpty = barFull + 8 * NSLOT;
    const uint64_t d0_ = FULL ? make_desc(sb, 8192, 1024, 1) : make_desc(sb, 4096, 512, 2);
    const uint32_t dlo0 = (uint32_t)d0_, dhi = (uint32_t)(d0_ >> 32);
    const uint32_t peerEmpty = mapa(barEmpty, peer);
    int st = (T * 8) % NSLOT, ph = ((T * 8) / NSLOT) & 1;
    constexpr int UO = FULL ? 32 : 16;
    float acc[2 * UO];
#pragma unroll
    for (int i = 0; i < 2 * UO; i++) acc[i] = 0.f;
#pragma unroll
    for (int kb = 0; kb < 8; kb++) {
        mbar_wait(barFull + 8 * st, ph);
        wgmma_fence();
        const uint32_t dlo = dlo0 + st * (SLOT / 16);
        if (FULL) {
            wgmma_rst_n128<0>(acc, a[4 * kb], dlo, dhi); wgmma_rst_n128<128>(acc, a[4 * kb + 1], dlo, dhi);
            wgmma_rst_n128<256>(acc, a[4 * kb + 2], dlo, dhi); wgmma_rst_n128<384>(acc, a[4 * kb + 3], dlo, dhi);
        } else {
            wgmma_rst_n64<0>(acc, a[4 * kb], dlo, dhi); wgmma_rst_n64<64>(acc, a[4 * kb + 1], dlo, dhi);
            wgmma_rst_n64<128>(acc, a[4 * kb + 2], dlo, dhi); wgmma_rst_n64<192>(acc, a[4 * kb + 3], dlo, dhi);
        }
        wgmma_commit();
        if (kb == G1_LAG) asm volatile("{\n.reg .pred p;\nsetp.eq.s32 p, %0, 0;\n@p bar.arrive 5, 256;\n}\n" ::"r"(wg + T) : "memory");
        if (kb > 0) {
            wgmma_wait<1>();
            if ((tid & 127) == 0) {
                const int pst = (st == 0) ? NSLOT - 1 : st - 1;
                mbar_arrive(barEmpty + 8 * pst);
                mbar_arrive_cluster(peerEmpty + 8 * pst);
            }
        }
        if (++st == NSLOT) { st = 0; ph ^= 1; }
    }
    wgmma_wait<0>();
    if ((tid & 127) == 0) {
        const int pst = (st == 0) ? NSLOT - 1 : st - 1;
        mbar_arrive(barEmpty + 8 * pst);
        mbar_arrive_cluster(peerEmpty + 8 * pst);
    }
    TS(1, 3 + 2 * T, tid == 0);
    TS(2, 12 + T, tid == 128);
    constexpr int NJ = FULL ? 8 : 4;
    uint32_t pk[NJ][2];
#pragma unroll
    for (int j = 0; j < NJ; j++) {
#pragma unroll
        for (int hf = 0; hf < 2; hf++) {
            const float inv = hf ? inv1 : inv0;
            const uint32_t gp = pack_bf16(acc[4 * j + 2 * hf] * inv, acc[4 * j + 2 * hf + 1] * inv);
            const uint32_t up = pack_bf16(acc[UO + 4 * j + 2 * hf] * inv, acc[UO + 4 * j + 2 * hf + 1] * inv);
            const uint32_t sp = pack_bf16(sigmoid_f(bf_lo(gp)), sigmoid_f(bf_hi(gp)));
            const bf162 pr = __hmul2_rn(*reinterpret_cast<const bf162*>(&sp), *reinterpret_cast<const bf162*>(&up));
            pk[j][hf] = *reinterpret_cast<const uint32_t*>(&pr);
        }
    }
    const int ns = f0;
    const int blk = 14 * (ns >> 2) + (FULL ? 4 * T + (ns & 3) : 12 + ((ns & 3) >> 1));
    uint4* dst = reinterpret_cast<uint4*>(g_hh) + ((size_t)(row0 >> 7) * 28 + blk) * 1024 + warp * 128 + (FULL ? 0 : (ns & 1) * 64) + lane;
#pragma unroll
    for (int j = 0; j < NJ; j += 2) dst[(j >> 1) * 32] = make_uint4(pk[j][0], pk[j][1], pk[j + 1][0], pk[j + 1][1]);
    asm volatile("bar.arrive %0, 160;" ::"r"(11 + wg) : "memory");
    TS(1, 4 + 2 * T, tid == 0);
}

constexpr int NA = 6;
__device__ __forceinline__ int g2_slotB(int j) { return 4 + (j & 7); }
__device__ __forceinline__ int g2_fillB(int j) { return 2 + (j >> 3); }
__device__ __forceinline__ int g2_slotA(int j) { return (12 + j % NA) % NSLOT; }
__device__ __forceinline__ int g2_fillA(int j) { return (j % NA < 2 ? 2 : 3) + j / NA; }

__global__ void __cluster_dims__(2, 1, 1) __launch_bounds__(512, 1)
mega_kernel(const bf16* __restrict__ xin, const bf16* __restrict__ kin, const bf16* __restrict__ vin, const bf16* __restrict__ shift_k,
            const bf16* __restrict__ ssm_k, const bf16* __restrict__ ssm_D,
            const bf16* __restrict__ w_gate, const bf16* __restrict__ w_up, const bf16* __restrict__ w_down, bf16* __restrict__ out,
            const __grid_constant__ CUtensorMap map_g, const __grid_constant__ CUtensorMap map_u,
            const __grid_constant__ CUtensorMap map_g32, const __grid_constant__ CUtensorMap map_u32,
            const __grid_constant__ CUtensorMap map_d, const __grid_constant__ CUtensorMap map_d32, const __grid_constant__ CUtensorMap map_k, const __grid_constant__ CUtensorMap map_kh,
            const __grid_constant__ CUtensorMap map_v, const __grid_constant__ CUtensorMap map_x) {
    extern __shared__ uint8_t smem_raw[];
    uint8_t* smem = smem_raw + ((1024u - (smem_u32(smem_raw) & 1023u)) & 1023u);
    const uint32_t sb = smem_u32(smem);
    const uint32_t barFull = sb + BAR_OFF, barEmpty = barFull + 8 * NSLOT, barA = barEmpty + 8 * NSLOT;
    const uint32_t barKV = barA + 64, barXS = barKV + 8, barX = barXS + 8, barKin = barX + 8, barXin = barKin + 8, barAE = barXin + 8, barG1 = barAE + 48, barRdy = barG1 + 8, barKi = barRdy + 8;
    const int tid = threadIdx.x, warp = tid >> 5, lane = tid & 31;
    const int bid = blockIdx.x;
    const int rank = bid & 1;
    const int d0 = bid * 4, dp = (bid >> 1) * 8;
    const int ns = (bid >> 1) & 7, mt1 = 2 * (bid >> 4) + rank;
    const int f0 = ns * 224;
    const int mt2 = bid >> 3, nt = (bid >> 1) & 3;
    TS_INIT();
    TS(0, 0, tid == 0);

    if (tid == 0) {
        for (int i = 0; i < NSLOT; i++) { mbar_init(barFull + 8 * i, 1); mbar_init(barEmpty + 8 * i, 4); }
        for (int i = 0; i < 8; i++) mbar_init(barA + 8 * i, 1);
        mbar_init(barKV, 1);
        mbar_init(barXS, 2);
        mbar_init(barX, 1);
        for (int i = 0; i < NA; i++) mbar_init(barAE + 8 * i, 8);
        mbar_init(barRdy, 2);
        mbar_init(barG1, 1);
        for (int i = 0; i < 4; i++) mbar_init(barKi + 8 * i, 1);
        mbar_init(barKin, 1);
        mbar_init(barXin, 1);
        asm volatile("fence.mbarrier_init.release.cluster;" ::: "memory");
        mbar_expect_tx(barKV, 16384);
        mbar_expect_tx(barXS, 16384);
        mbar_expect_tx(barX, 32768);
        for (int i = 0; i < 4; i++) {
            mbar_expect_tx(barKi + 8 * i, i == 0 ? 8192 + 128 : 8192);
            if (i == 0) tma_load_2d(sb + CV_KS_OFF + 896, &map_kh, barKi, dp, 1024 * rank - 8);
            tma_load_2d(sb + CV_KS_OFF + 1024 + i * 4096, &map_k, barKi + 8 * i, dp, 1024 * rank + 256 * i);
            tma_load_2d(sb + CV_VS_OFF + i * 4096, &map_v, barKi + 8 * i, dp, 1024 * rank + 256 * i);
        }
        mbar_expect_tx(barXin, 16384);
        for (int i = 0; i < 4; i++) tma_load_2d(sb + CV_XI_OFF + i * 4096, &map_x, barXin, dp, 1024 * rank + 256 * i);
    }
    __syncwarp();
    asm volatile("barrier.cluster.arrive.relaxed.aligned;" ::: "memory");
    const uint2 dD = __ldg(reinterpret_cast<const uint2*>(ssm_D + d0));

    if (tid < 256) {
        uint32_t w[4][4];
#pragma unroll
        for (int cp = 0; cp < 4; cp++) {
            const uint4 sw = __ldg(reinterpret_cast<const uint4*>(shift_k + (dp + 2 * cp) * 4));
            w[0][cp] = __byte_perm(sw.x, sw.z, 0x5410); w[1][cp] = __byte_perm(sw.x, sw.z, 0x7632);
            w[2][cp] = __byte_perm(sw.y, sw.w, 0x5410); w[3][cp] = __byte_perm(sw.y, sw.w, 0x7632);
        }
        asm volatile("bar.sync 1, 512;" ::: "memory");
        cluster_wait();
        const int g = lane >> 2, t = lane & 3;
        const uint32_t dbase = mapa(sb, g >> 2);
#pragma unroll 1
        for (int i = 0; i < 4; i++) {
            mbar_wait(barKi + 8 * i, 0);
            const int row = tid + 256 * i;
            const uint4* ks = reinterpret_cast<const uint4*>(smem + CV_KS_OFF + 1024) + row;
            uint4* vs = reinterpret_cast<uint4*>(smem + CV_VS_OFF) + row;
            const uint4 k0 = ks[-3], k1 = ks[-2], k2 = ks[-1], k3 = ks[0], vv = vs[0];
            const uint32_t ka[4][4] = {{k0.x, k0.y, k0.z, k0.w}, {k1.x, k1.y, k1.z, k1.w}, {k2.x, k2.y, k2.z, k2.w}, {k3.x, k3.y, k3.z, k3.w}};
            const uint32_t va[4] = {vv.x, vv.y, vv.z, vv.w};
            uint32_t o[4];
#pragma unroll
            for (int cp = 0; cp < 4; cp++) {
                bf162 acc2 = __hmul2_rn(*reinterpret_cast<const bf162*>(&ka[0][cp]), *reinterpret_cast<const bf162*>(&w[3][cp]));
#pragma unroll
                for (int t = 1; t < 4; t++)
                    acc2 = __hadd2_rn(acc2, __hmul2_rn(*reinterpret_cast<const bf162*>(&ka[t][cp]), *reinterpret_cast<const bf162*>(&w[3 - t][cp])));
                acc2 = __hmul2_rn(acc2, *reinterpret_cast<const bf162*>(&va[cp]));
                o[cp] = *reinterpret_cast<uint32_t*>(&acc2);
            }
            vs[0] = make_uint4(o[0], o[1], o[2], o[3]);
            __syncwarp();
            const int row0 = 32 * warp + 256 * i;
            uint32_t c[4];
            load_chunk_t(sb + CV_VS_OFF + row0 * 16, lane, c);
            const int p = 128 * rank + (row0 >> 3) + t;
            st_async_v4(dbase + CV_BASE + (g & 3) * CV_CH_BYTES + ((p & 1) * CV_R + 127 - (p >> 1)) * 16, c, dbase + BAR_OFF + (barKV - barFull));
        }
    } else {
        const int u = tid - 256;
        const int lrow = bid * 16 + 2 * (u >> 5);
        const uint4* xp = reinterpret_cast<const uint4*>(xin + (size_t)lrow * D_ + lane * 16);
        uint4 xa[2], xb[2];
        xa[0] = __ldg(xp); xb[0] = __ldg(xp + 1); xa[1] = __ldg(xp + 64); xb[1] = __ldg(xp + 65);
        uint4 kk[4]; uint32_t prev[4];
#pragma unroll
        for (int c = 0; c < 4; c++) {
            const bf16* kp = ssm_k + (size_t)(d0 + c) * S_ + 8 * u;
            kk[c] = __ldg(reinterpret_cast<const uint4*>(kp));
            prev[c] = (u > 0) ? (uint32_t)__ldg(reinterpret_cast<const unsigned short*>(kp - 1)) : 0u;
        }
        asm volatile("bar.sync 1, 512;" ::: "memory");
        if (u < 224) *reinterpret_cast<uint4*>(smem + CV_BASE + (u / 56) * CV_CH_BYTES + (((u % 56) / 28) * CV_R + 128 + (u % 28)) * 16) = make_uint4(0, 0, 0, 0);
        if (u < 64) reinterpret_cast<uint32_t*>(smem + CV_BASE + (u >> 4) * CV_CH_BYTES + CV_XT_BYTES)[u & 15] = 0;
        else if (u < 128) reinterpret_cast<uint32_t*>(smem + ONES_OFF)[u - 64] = 0x3F803F80u;
#pragma unroll
        for (int c = 0; c < 4; c++) {
            uint4 lo, hi;
            lo.x = (kk[c].x & 0xffffu) | (prev[c] << 16);
            lo.y = __byte_perm(kk[c].x, 0, 0x1032);
            lo.z = __byte_perm(kk[c].y, kk[c].x, 0x7610);
            lo.w = __byte_perm(kk[c].y, 0, 0x1032);
            hi.x = __byte_perm(kk[c].z, kk[c].y, 0x7610);
            hi.y = __byte_perm(kk[c].z, 0, 0x1032);
            hi.z = __byte_perm(kk[c].w, kk[c].z, 0x7610);
            hi.w = __byte_perm(kk[c].w, 0, 0x1032);
            uint4* dst = reinterpret_cast<uint4*>(smem + CV_BASE + c * CV_CH_BYTES + CV_XT_BYTES + (16 + 8 * u) * 4);
            dst[0] = lo; dst[1] = hi;
        }
        fence_proxy_async();
        __syncwarp();
        asm volatile("bar.arrive 2, 512;" ::: "memory");
        asm volatile("bar.sync 3, 256;" ::: "memory");
#pragma unroll
        for (int r = 0; r < 2; r++) {
            const uint32_t xw[8] = {xa[r].x, xa[r].y, xa[r].z, xa[r].w, xb[r].x, xb[r].y, xb[r].z, xb[r].w};
            float sm_ = 0.f;
#pragma unroll
            for (int i = 0; i < 8; i++) sm_ += bf_lo(xw[i]) + bf_hi(xw[i]);
            sm_ = warp_sum(sm_);
            const float mean = sm_ * (1.f / 512.f);
            float q = 0.f;
#pragma unroll
            for (int i = 0; i < 8; i++) { float d1 = bf_lo(xw[i]) - mean, d2 = bf_hi(xw[i]) - mean; q += d1 * d1 + d2 * d2; }
            q = warp_sum(q);
            if (lane == 0) {
                g_stats[lrow + r] = pack_bf16(mean, sqrtf(bf16r(bf16r(q * (1.f / 512.f)) + 1e-5f)));
            }
        }
        if (lane == 0) {
            __threadfence();
            atomicAdd(&g_bar, 1u);
        }
        __syncwarp();
        cluster_wait();
        if (u == 32) {
            const CUtensorMap* mw = rank ? &map_u : &map_g;
            for (int it = 0; it < PRE; it++) {
                mbar_expect_tx(barFull + 8 * it, SLOT);
                tma_load_2d_mc(sb + it * SLOT + rank * 8192, mw, barFull + 8 * it, f0, 64 * it, (uint16_t)3);
            }
        }
    }
    TS(0, 1, tid == 0);
    mbar_wait(barKV, 0);
    fence_proxy_async();
    if (tid < 256) asm volatile("bar.sync 2, 512;" ::: "memory");

    const int wg = __shfl_sync(0xffffffffu, tid >> 7, 0);
    {
        const int wq = warp & 3, g = lane >> 2, t = lane & 3;
        uint8_t* chs = smem + CV_BASE + wg * CV_CH_BYTES;
        float acc[64];
#pragma unroll
        for (int i = 0; i < 64; i++) acc[i] = 0.f;
        const uint32_t* wp = reinterpret_cast<const uint32_t*>(chs + CV_XT_BYTES) + 16 + 16 * wq + g - 2 * t;
        conv_mma(acc, wp, smem_u32(chs));
        TS(0, 4 + wg, (tid & 127) == 0);
        if (wg < 2) {
            if (tid == 0) {
                wait_counter(&g_bar, 1024u);
                fence_proxy_async_global();
                mbar_expect_tx(barXS, 8192);
                asm volatile("cp.async.bulk.shared::cluster.global.mbarrier::complete_tx::bytes [%0], [%1], %2, [%3];"
                             ::"r"(sb + CV_ST_OFF), "l"(g_stats), "r"(8192), "r"(barXS) : "memory");
                constexpr int SH = D_ * F_ * 2 / 128;
                asm volatile("cp.async.bulk.prefetch.L2.global [%0], %1;" ::"l"(reinterpret_cast<const uint8_t*>(w_gate) + (size_t)bid * SH), "r"(SH) : "memory");
                asm volatile("cp.async.bulk.prefetch.L2.global [%0], %1;" ::"l"(reinterpret_cast<const uint8_t*>(w_up) + (size_t)bid * SH), "r"(SH) : "memory");
                asm volatile("cp.async.bulk.prefetch.L2.global [%0], %1;" ::"l"(reinterpret_cast<const uint8_t*>(w_down) + (size_t)bid * SH), "r"(SH) : "memory");
            }
            __syncwarp();
        }
        if (wg < 2) {
            const uint32_t dbase = mapa(sb, g >> 2);
            mbar_wait(barXin, 0);
#pragma unroll
            for (int i = 0; i < 4; i++) {
                const int row0 = 32 * warp + 256 * i;
                uint32_t c[4];
                load_chunk_t(sb + CV_XI_OFF + row0 * 16, lane, c);
                const int p = 128 * rank + (row0 >> 3) + t;
                st_async_v4(dbase + CV_XS_OFF + (g & 3) * CV_XS_PITCH + p * 16, c, dbase + BAR_OFF + (barXS - barFull));
            }
            asm volatile("bar.arrive 10, 384;" ::: "memory");
        }
        if (wg == 2) asm volatile("bar.sync 10, 384;" ::: "memory");
        const uint32_t pbase = smem_u32(chs + CV_XT_BYTES + CV_WT_BYTES + (wq & 1) * CV_P_BYTES);
        uint32_t pa[4];
        bool ok0[4];
#pragma unroll
        for (int e = 0; e < 4; e++) {
            const int s = 16 * (127 - 2 * t) + 16 * wq + g - 16 * (e & 1) + 8 * (e >> 1);
            pa[e] = pbase + (s + 4 * (s >> 3)) * 4;
            ok0[e] = s < S_;
        }
        if (wq < 2) {
#pragma unroll
            for (int i = 0; i < 64; i++) {
                const int e = (i & 1) | (i & 2);
                if (i >= 4 || ok0[e]) asm volatile("st.shared.f32 [%0], %1;" ::"r"(pa[e] - 768 * (i >> 2)), "f"(acc[i]) : "memory");
            }
            if (wq == 1 && lane < 16) asm volatile("st.shared.f32 [%0], %1;" ::"r"(pbase + (lane + 4 * (lane >> 3)) * 4), "f"(0.f) : "memory");
        }
        asm volatile("bar.sync %0, 128;" ::"r"(6 + wg) : "memory");
        if (wq >= 2) {
#pragma unroll
            for (int i0 = 0; i0 < 64; i0 += 16) {
                float o[16];
#pragma unroll
                for (int i = i0; i < i0 + 16; i++) {
                    const int e = (i & 1) | (i & 2);
                    o[i - i0] = 0.f;
                    if (i >= 4 || ok0[e]) asm volatile("ld.shared.f32 %0, [%1];" : "=f"(o[i - i0]) : "r"(pa[e] - 768 * (i >> 2)));
                }
#pragma unroll
                for (int i = i0; i < i0 + 16; i++) {
                    const int e = (i & 1) | (i & 2);
                    if (i >= 4 || ok0[e]) asm volatile("st.shared.f32 [%0], %1;" ::"r"(pa[e] - 768 * (i >> 2)), "f"(o[i - i0] + acc[i]) : "memory");
                }
            }
        }
    }
    TS(0, 10, tid == 0);
    TS(0, 11, tid == 480);
    mbar_wait(barXS, 0);
    asm volatile("bar.sync %0, 128;" ::"r"(6 + wg) : "memory");
    TS(0, 8, tid == 0);
    {
        const int c = wg, lt = tid & 127;
        const uint8_t* cb = smem + CV_BASE + c * CV_CH_BYTES;
        const uint32_t dw = (c & 2) ? dD.y : dD.x;
        const float Dv = (c & 1) ? bf_hi(dw) : bf_lo(dw);
#pragma unroll
        for (int it = 0; it < 2; it++) {
            const int p = lt + 128 * it;
            const int s0 = 8 * p;
            const float4* p0 = reinterpret_cast<const float4*>(cb + CV_XT_BYTES + CV_WT_BYTES + p * 48);
            const float4* p1 = reinterpret_cast<const float4*>(cb + CV_XT_BYTES + CV_WT_BYTES + CV_P_BYTES + p * 48);
            const uint4 kv = *reinterpret_cast<const uint4*>(cb + ((p & 1) * CV_R + 127 - (p >> 1)) * 16);
            const uint4 xv = *reinterpret_cast<const uint4*>(smem + CV_XS_OFF + c * CV_XS_PITCH + p * 16);
            const uint4 sa_ = *reinterpret_cast<const uint4*>(smem + CV_ST_OFF + s0 * 4), sb_ = *reinterpret_cast<const uint4*>(smem + CV_ST_OFF + s0 * 4 + 16);
            const uint32_t sw_[8] = {sa_.x, sa_.y, sa_.z, sa_.w, sb_.x, sb_.y, sb_.z, sb_.w};
            const float4 a0 = p0[0], a1 = p0[1], b0 = p1[0], b1 = p1[1];
            float y[8] = {a0.x + b0.x, a0.y + b0.y, a0.z + b0.z, a0.w + b0.w, a1.x + b1.x, a1.y + b1.y, a1.z + b1.z, a1.w + b1.w};
            const uint32_t kw[4] = {kv.x, kv.y, kv.z, kv.w};
            const uint32_t xw[4] = {xv.x, xv.y, xv.z, xv.w};
            uint32_t ow[4];
#pragma unroll
            for (int j = 0; j < 4; j++) {
                float e0 = bf_lo(kw[j]) * Dv, e1 = bf_hi(kw[j]) * Dv;
                bf16r2(e0, e1);
                bf16r2(y[2 * j], y[2 * j + 1]);
                const uint32_t zp = pack_bf16(y[2 * j] + e0, y[2 * j + 1] + e1);
                float q0 = bf_lo(xw[j]) - bf_lo(sw_[2 * j]), q1 = bf_hi(xw[j]) - bf_lo(sw_[2 * j + 1]);
                bf16r2(q0, q1);
                const uint32_t qp = pack_bf16(__fdividef(q0, bf_hi(sw_[2 * j])), __fdividef(q1, bf_hi(sw_[2 * j + 1])));
                const bf162 qz = __hmul2_rn(*reinterpret_cast<const bf162*>(&qp), *reinterpret_cast<const bf162*>(&zp));
                const bf162 hv = __hadd2_rn(*reinterpret_cast<const bf162*>(&xw[j]), qz);
                ow[j] = *reinterpret_cast<const uint32_t*>(&hv);
            }
            TS(0, 13, tid == 0 && it == 0);
            asm volatile("st.global.v4.u32 [%0], {%1,%2,%3,%4};" ::"l"(g_hb + (size_t)(p >> 1) * (D_ * 16) + (d0 + c) * 16 + ((p & 1) ^ rank) * 8),
                         "r"(ow[0]), "r"(ow[1]), "r"(ow[2]), "r"(ow[3]) : "memory");
            TS(0, 14, tid == 0 && it == 0);
        }
    }
    TS(0, 12, tid == 0);
    asm volatile("bar.sync %0, 128;" ::"r"(6 + wg) : "memory");
    if ((tid & 127) == 96) {
        __threadfence();
        atomicAdd(&g_c1, 1u);
    }
    fence_proxy_async();
    __syncthreads();
    TS(0, 9, tid == 0);

    if (wg >= 2) {
        asm volatile("setmaxnreg.dec.sync.aligned.u32 24;");
        if (warp == 12 || warp == 13) {
            for (int T = 0; T < 4; T++) {
                asm volatile("bar.sync %0, 160;" ::"r"(warp - 1) : "memory");
                if (lane == 0) {
                    __threadfence();
                    atomicAdd(&g_c2[(mt1 * 2 + (ns >> 2)) * 4 + T], 1u);
                }
                __syncwarp();
            }
        }
        if (tid == 256) {
            for (int i = 0; i < 3; i++) {
                const uint32_t e = barEmpty + 8 * (PRE + i);
                asm volatile("mbarrier.arrive.shared::cta.b64 _, [%0], 2;" ::"r"(e) : "memory");
                asm volatile("mbarrier.arrive.shared::cluster.b64 _, [%0], 2;" ::"r"(mapa(e, rank ^ 1)) : "memory");
            }
            wait_counter(&g_c1, 512u);
            fence_proxy_async_global();
            TS(1, 11, true);
            for (int i = 0; i < 8; i++) {
                mbar_expect_tx(barA + 8 * i, 16384);
                asm volatile("cp.async.bulk.shared::cluster.global.mbarrier::complete_tx::bytes [%0], [%1], %2, [%3];"
                             ::"r"(sb + (A_SLOT0 + i) * SLOT), "l"(g_hb + (size_t)(mt1 * 8 + i) * (D_ * 16)), "r"(16384), "r"(barA + 8 * i) : "memory");
            }
            for (int T = 0; T < 2; T++) wait_counter(&g_c2[(2 * mt2 + rank) * 4 + T], 8u);
            fence_proxy_async_global();
            mbar_wait(barG1, 0);
            for (int j = 0; j < 14; j++) {
                const int st = g2_slotA(j), f = g2_fillA(j);
                if (j == 8 || j == 12) {
                    wait_counter(&g_c2[(2 * mt2 + rank) * 4 + (j >> 2)], 8u);
                    fence_proxy_async_global();
                }
                if (j < NA) mbar_wait(barEmpty + 8 * st, (f - (st < PRE ? 1 : 0)) & 1);
                else mbar_wait(barAE + 8 * (j % NA), (j / NA - 1) & 1);
                mbar_expect_tx(barFull + 8 * st, SLOT);
                asm volatile("cp.async.bulk.shared::cluster.global.mbarrier::complete_tx::bytes [%0], [%1], %2, [%3];"
                             ::"r"(sb + st * SLOT), "l"(reinterpret_cast<const uint8_t*>(g_hh) + ((size_t)mt2 * 28 + rank * 14 + j) * 16384), "r"(16384), "r"(barFull + 8 * st) : "memory");
            }
        } else if (tid == 288) {
            const CUtensorMap* mw = rank ? &map_u : &map_g;
            for (int it = PRE; it < 32; it++) {
                const int st = it % NSLOT, f = it / NSLOT;
                mbar_wait(barEmpty + 8 * st, (f - (st < PRE ? 1 : 0)) & 1);
                if (it < 24) {
                    mbar_expect_tx(barFull + 8 * st, SLOT);
                    tma_load_2d_mc(sb + st * SLOT + rank * 8192, mw, barFull + 8 * st, f0 + 64 * (it >> 3), 64 * (it & 7), (uint16_t)3);
                } else {
                    mbar_expect_tx(barFull + 8 * st, SLOT / 2);
                    tma_load_2d_mc(sb + st * SLOT + rank * 4096, rank ? &map_u32 : &map_g32, barFull + 8 * st, f0 + 192, 64 * (it & 7), (uint16_t)3);
                }
            }
            mbar_arrive(barG1);
            const int c0 = nt * 128, k0 = rank * 896;
            for (int j = 0; j < 14; j++) {
                const int st = g2_slotB(j), f = g2_fillB(j);
                mbar_wait(barEmpty + 8 * st, (f - (st < PRE ? 1 : 0)) & 1);
                mbar_expect_tx(barFull + 8 * st, SLOT);
                if (j < 12) {
                    const int kr = k0 + 224 * (j & 3) + 64 * (j >> 2);
                    tma_load_2d(sb + st * SLOT, &map_d, barFull + 8 * st, c0, kr);
                    tma_load_2d(sb + st * SLOT + 8192, &map_d, barFull + 8 * st, c0 + 64, kr);
                } else {
                    const int kr = k0 + 448 * (j - 12) + 192;
                    tma_load_2d(sb + st * SLOT, &map_d32, barFull + 8 * st, c0, kr);
                    tma_load_2d(sb + st * SLOT + 4096, &map_d32, barFull + 8 * st, c0, kr + 224);
                    tma_load_2d(sb + st * SLOT + 8192, &map_d32, barFull + 8 * st, c0 + 64, kr);
                    tma_load_2d(sb + st * SLOT + 12288, &map_d32, barFull + 8 * st, c0 + 64, kr + 224);
                }
            }
        }
    } else {
        asm volatile("setmaxnreg.inc.sync.aligned.u32 232;");
        const int row1 = mt1 * 128;
        {
            uint32_t a[32][4];
            {
                const uint32_t abase = sb + (A_SLOT0 + warp) * SLOT + ((lane & 7) + 8 * (lane >> 4)) * 32 + (((lane >> 3) ^ (lane >> 2)) & 1) * 16;
                mbar_wait(barA + 8 * warp, 0);
                TS(1, 12, tid == 0);
#pragma unroll
                for (int kk = 0; kk < 32; kk++) {
                    asm volatile("ldmatrix.sync.aligned.m8n8.x4.trans.shared.b16 {%0,%1,%2,%3}, [%4];"
                                 : "=r"(a[kk][0]), "=r"(a[kk][1]), "=r"(a[kk][2]), "=r"(a[kk][3])
                                 : "r"(abase + kk * 512) : "memory");
                }
            }
            TS(1, 14, tid == 0);
            float inv0, inv1;
            {
                float rs[4] = {0.f, 0.f, 0.f, 0.f};
                const uint64_t dones = make_desc(sb + ONES_OFF, 128, 128, 0);
                wgmma_fence();
#pragma unroll
                for (int kk = 0; kk < 32; kk++) wgmma_rs_n8<0>(rs, a[kk][0], a[kk][1], a[kk][2], a[kk][3], (uint32_t)dones, (uint32_t)(dones >> 32));
                wgmma_commit();
                float ga = 0.f, gb = 0.f, gc = 0.f, gd = 0.f;
#pragma unroll
                for (int kk = 0; kk < 32; kk++) {
                    float l, h;
                    l = bf_lo(a[kk][0]); h = bf_hi(a[kk][0]); ga += l * l; gc += h * h;
                    l = bf_lo(a[kk][2]); h = bf_hi(a[kk][2]); ga += l * l; gc += h * h;
                    l = bf_lo(a[kk][1]); h = bf_hi(a[kk][1]); gb += l * l; gd += h * h;
                    l = bf_lo(a[kk][3]); h = bf_hi(a[kk][3]); gb += l * l; gd += h * h;
                }
                ga += gc; gb += gd;
                ga += __shfl_xor_sync(0xffffffffu, ga, 1); ga += __shfl_xor_sync(0xffffffffu, ga, 2);
                gb += __shfl_xor_sync(0xffffffffu, gb, 1); gb += __shfl_xor_sync(0xffffffffu, gb, 2);
                wgmma_wait<0>();
                if (lane == 0) {
                    const uint32_t e = barEmpty + 8 * (A_SLOT0 + warp);
                    asm volatile("mbarrier.arrive.shared::cta.b64 _, [%0], 2;" ::"r"(e) : "memory");
                    asm volatile("mbarrier.arrive.shared::cluster.b64 _, [%0], 2;" ::"r"(mapa(e, rank ^ 1)) : "memory");
                }
                const float mean0 = rs[0] * (1.f / 512.f), mean1 = rs[2] * (1.f / 512.f);
                const uint32_t mp = pack_bf16(mean0, mean1);
                const uint32_t m0 = __byte_perm(mp, 0, 0x1010), m1 = __byte_perm(mp, 0, 0x3232);
#pragma unroll
                for (int kk = 0; kk < 32; kk++) {
#pragma unroll
                    for (int r = 0; r < 4; r++) {
                        const uint32_t mm = (r & 1) ? m1 : m0;
                        const bf162 dd = __hsub2_rn(*reinterpret_cast<const bf162*>(&a[kk][r]), *reinterpret_cast<const bf162*>(&mm));
                        a[kk][r] = *reinterpret_cast<const uint32_t*>(&dd);
                    }
                }
                const float v0 = fmaxf(ga * (1.f / 512.f) - mean0 * mean0, 0.f), v1 = fmaxf(gb * (1.f / 512.f) - mean1 * mean1, 0.f);
                inv0 = __fdividef(1.f, bf16r(sqrtf(bf16r(bf16r(v0) + 1e-5f))));
                inv1 = __fdividef(1.f, bf16r(sqrtf(bf16r(bf16r(v1) + 1e-5f))));
            }
            TS(1, 2, tid == 0);
            if (wg == 1) asm volatile("bar.sync 5, 256;" ::: "memory");
#pragma unroll 1
            for (int T = 0; T < 3; T++) gemm1_pass<true>(T, a, inv0, inv1, sb, rank ^ 1, row1, ns, tid, wg);
            gemm1_pass<false>(3, a, inv0, inv1, sb, rank ^ 1, row1, ns, tid, wg);
        }
        TS(2, 0, tid == 0);

        {
        uint32_t sb_, tid_;
        asm volatile("mov.u32 %0, %1;" : "=r"(sb_) : "r"(sb) : "memory");
        asm volatile("mov.u32 %0, %%tid.x;" : "=r"(tid_) :: "memory");
        const uint32_t sb = sb_;
        const int tid = (int)tid_, warp = tid >> 5, lane = tid & 31;
        const uint32_t barFull = sb + BAR_OFF, barEmpty = barFull + 8 * NSLOT, barA = barEmpty + 8 * NSLOT;
        const uint32_t barX = barA + 64 + 16, barAE = barX + 24, barRdy = barAE + 56;
        const int c0 = nt * 128, row2 = mt2 * 128;
        float acc[64];
#pragma unroll
        for (int i = 0; i < 64; i++) acc[i] = 0.f;
        {
            uint32_t a[2][4][4];
            const uint64_t d0_ = make_desc(sb, 8192, 1024, 1);
            const uint32_t dlo0 = (uint32_t)d0_, dhi = (uint32_t)(d0_ >> 32);
            const uint32_t abase = sb + warp * 2048 + lane * 16;
#pragma unroll
            for (int j = 0; j < 14; j++) {
                const int jj = j & 1;
                const int sa = g2_slotA(j), sbk = g2_slotB(j);
                mbar_wait(barFull + 8 * sa, g2_fillA(j) & 1);
                if (j >= 2) {
                    wgmma_wait<1>();
                    if (j < 8 && (tid & 127) == 0) asm volatile("mbarrier.arrive.shared::cta.b64 _, [%0], 2;" ::"r"(barEmpty + 8 * g2_slotB(j - 2)) : "memory");
                    if (j == 9 && (tid & 127) == 0) mbar_arrive_cluster(mapa(barRdy, rank ^ 1));
                }
#pragma unroll
                for (int kk = 0; kk < 4; kk++)
                    asm volatile("ld.shared.v4.u32 {%0,%1,%2,%3}, [%4];" : "=r"(a[jj][kk][0]), "=r"(a[jj][kk][1]), "=r"(a[jj][kk][2]), "=r"(a[jj][kk][3])
                                 : "r"(abase + sa * SLOT + kk * 512) : "memory");
                mbar_wait(barFull + 8 * sbk, g2_fillB(j) & 1);
                if ((j & 1) == 0) TS(2, 5 + (j >> 1), tid == 128);
                wgmma_fence();
                const uint32_t dlo = dlo0 + sbk * (SLOT / 16);
                wgmma_rst_n128<0>(acc, a[jj][0], dlo, dhi); wgmma_rst_n128<128>(acc, a[jj][1], dlo, dhi);
                wgmma_rst_n128<256>(acc, a[jj][2], dlo, dhi); wgmma_rst_n128<384>(acc, a[jj][3], dlo, dhi);
                wgmma_commit();
                if (j < 14 - NA) {
                    __syncwarp();
                    if (lane == 0) asm volatile("mbarrier.arrive.shared::cta.b64 _, [%0];" ::"r"(barAE + 8 * (j % NA)) : "memory");
                }
            }
        }
        uint4 hv[4];
        {
            const uint4* hsrc = reinterpret_cast<const uint4*>(g_hb + (size_t)(mt2 * 8 + warp) * (D_ * 16) + (c0 + 64 * rank) * 16);
#pragma unroll
            for (int i = 0; i < 4; i++) hv[i] = __ldcg(hsrc + lane + 32 * i);
        }
        wgmma_wait<0>();
        TS(2, 1 + wg, (tid & 127) == 0);
        {
            const uint32_t dst = mapa(sb + X_OFF + tid * 16, rank ^ 1);
            const uint32_t dbar = mapa(barX, rank ^ 1);
            mbar_wait(barRdy, 0);
#pragma unroll
            for (int j = 0; j < 8; j++) {
                uint32_t v[4];
#pragma unroll
                for (int e = 0; e < 4; e++) v[e] = __float_as_uint(rank == 0 ? acc[32 + 4 * j + e] : acc[4 * j + e]);
                st_async_v4(dst + j * 4096, v, dbar);
            }
        }
        asm volatile("bar.sync 4, 256;" ::: "memory");
        const uint32_t stg = sb + warp * 2048;
#pragma unroll
        for (int i = 0; i < 4; i++)
            asm volatile("st.shared.v4.u32 [%0], {%1,%2,%3,%4};" ::"r"(stg + (lane + 32 * i) * 16), "r"(hv[i].x), "r"(hv[i].y), "r"(hv[i].z), "r"(hv[i].w) : "memory");
        __syncwarp();
        uint32_t hf_[8][2];
#pragma unroll
        for (int j = 0; j < 8; j += 2) {
            asm volatile("ldmatrix.sync.aligned.m8n8.x4.trans.shared.b16 {%0,%1,%2,%3}, [%4];"
                         : "=r"(hf_[j][0]), "=r"(hf_[j][1]), "=r"(hf_[j + 1][0]), "=r"(hf_[j + 1][1])
                         : "r"(stg + (8 * j + (lane & 7) + 8 * (lane >> 4)) * 32 + (((lane >> 3) ^ (lane >> 2)) & 1) * 16) : "memory");
        }
        __syncwarp();
        mbar_wait(barX, 0);
        uint32_t po[8][2];
#pragma unroll
        for (int j = 0; j < 8; j++) {
            float4 v;
            asm volatile("ld.shared.v4.f32 {%0,%1,%2,%3}, [%4];" : "=f"(v.x), "=f"(v.y), "=f"(v.z), "=f"(v.w) : "r"(sb + X_OFF + tid * 16 + j * 4096));
            float o0, o1, o2, o3;
            if (rank == 0) { o0 = acc[4 * j] + v.x; o1 = acc[4 * j + 1] + v.y; o2 = acc[4 * j + 2] + v.z; o3 = acc[4 * j + 3] + v.w; }
            else { o0 = acc[32 + 4 * j] + v.x; o1 = acc[33 + 4 * j] + v.y; o2 = acc[34 + 4 * j] + v.z; o3 = acc[35 + 4 * j] + v.w; }
            bf16r2(o0, o1); bf16r2(o2, o3);
            po[j][0] = pack_bf16(bf_lo(hf_[j][0]) + o0, bf_hi(hf_[j][0]) + o1);
            po[j][1] = pack_bf16(bf_lo(hf_[j][1]) + o2, bf_hi(hf_[j][1]) + o3);
        }
        const int mi = lane >> 3, rr = lane & 7;
#pragma unroll
        for (int j = 0; j < 8; j += 2) {
            const int row = rr + 8 * (mi & 1);
            const int chunk = j + (mi >> 1);
            stmatrix_x4(stg + row * 128 + ((chunk ^ (row & 7)) * 16), po[j][0], po[j][1], po[j + 1][0], po[j + 1][1]);
        }
        __syncwarp();
        const size_t obase = (size_t)(row2 + 16 * warp) * D_ + c0 + 64 * rank;
#pragma unroll
        for (int i = 0; i < 4; i++) {
            const int row = 4 * i + (lane >> 3), chunk = lane & 7;
            uint4 v;
            asm volatile("ld.shared.v4.u32 {%0,%1,%2,%3}, [%4];" : "=r"(v.x), "=r"(v.y), "=r"(v.z), "=r"(v.w) : "r"(stg + row * 128 + ((chunk ^ (row & 7)) * 16)));
            *reinterpret_cast<uint4*>(out + obase + (size_t)row * D_ + chunk * 8) = v;
        }
        TS(2, 3 + wg, (tid & 127) == 0);
        if (warp == 0) {
            unsigned int last = 0;
            if (lane == 0) last = (atomicAdd(&g_c3, 1u) == 127u);
            last = __shfl_sync(0xffffffffu, last, 0);
            if (last) {
                reinterpret_cast<uint4*>(g_c2)[lane] = make_uint4(0u, 0u, 0u, 0u);
                if (lane == 0) { g_c1 = 0u; g_bar = 0u; g_c3 = 0u; }
            }
        }
        }
    }
}

typedef CUresult (*PFN_encodeTiled)(CUtensorMap*, CUtensorMapDataType, cuuint32_t, void*, const cuuint64_t*, const cuuint64_t*,
                                    const cuuint32_t*, const cuuint32_t*, CUtensorMapInterleave, CUtensorMapSwizzle,
                                    CUtensorMapL2promotion, CUtensorMapFloatOOBfill);

static void make_map(PFN_encodeTiled enc, CUtensorMap* m, const void* ptr, uint64_t inner, uint64_t outer, uint32_t box_inner, uint32_t box_outer,
                     CUtensorMapSwizzle swz = CU_TENSOR_MAP_SWIZZLE_128B) {
    cuuint64_t dims[2] = {inner, outer};
    cuuint64_t strides[1] = {inner * 2};
    cuuint32_t box[2] = {box_inner, box_outer};
    cuuint32_t es[2] = {1, 1};
    enc(m, CU_TENSOR_MAP_DATA_TYPE_BFLOAT16, 2, const_cast<void*>(ptr), dims, strides, box, es, CU_TENSOR_MAP_INTERLEAVE_NONE,
        swz, CU_TENSOR_MAP_L2_PROMOTION_L2_256B, CU_TENSOR_MAP_FLOAT_OOB_FILL_NONE);
}

extern "C" void kernel_launch(void* const* d_in, const int* in_sizes, int n_in, void* d_out, int out_size) {
    const bf16* A_q = (const bf16*)d_in[0];
    const bf16* A_k = (const bf16*)d_in[1];
    const bf16* A_v = (const bf16*)d_in[2];
    const bf16* A_shift = (const bf16*)d_in[3];
    const bf16* A_ssmk = (const bf16*)d_in[4];
    const bf16* A_ssmD = (const bf16*)d_in[5];
    const bf16* w_gate = (const bf16*)d_in[7];
    const bf16* w_up = (const bf16*)d_in[8];
    const bf16* w_down = (const bf16*)d_in[9];

    static bool init = false;
    static CUtensorMap map_g, map_u, map_g32, map_u32, map_d, map_d32, map_k, map_kh, map_v, map_x;
    static const void* cached[6] = {nullptr, nullptr, nullptr, nullptr, nullptr, nullptr};
    if (!init || cached[0] != w_gate || cached[1] != w_up || cached[2] != w_down || cached[3] != A_q || cached[4] != A_k || cached[5] != A_v) {
        void* fn = nullptr;
        cudaDriverEntryPointQueryResult qres;
        cudaGetDriverEntryPoint("cuTensorMapEncodeTiled", &fn, cudaEnableDefault, &qres);
        PFN_encodeTiled enc = (PFN_encodeTiled)fn;
        make_map(enc, &map_g, w_gate, F_, D_, 64, 64);
        make_map(enc, &map_u, w_up, F_, D_, 64, 64);
        make_map(enc, &map_g32, w_gate, F_, D_, 32, 64, CU_TENSOR_MAP_SWIZZLE_64B);
        make_map(enc, &map_u32, w_up, F_, D_, 32, 64, CU_TENSOR_MAP_SWIZZLE_64B);
        make_map(enc, &map_d, w_down, D_, F_, 64, 64);
        make_map(enc, &map_d32, w_down, D_, F_, 64, 32);
        make_map(enc, &map_k, A_k, D_, S_, 8, 256, CU_TENSOR_MAP_SWIZZLE_NONE);
        make_map(enc, &map_kh, A_k, D_, S_, 8, 8, CU_TENSOR_MAP_SWIZZLE_NONE);
        make_map(enc, &map_v, A_v, D_, S_, 8, 256, CU_TENSOR_MAP_SWIZZLE_NONE);
        make_map(enc, &map_x, A_q, D_, S_, 8, 256, CU_TENSOR_MAP_SWIZZLE_NONE);
        cudaFuncSetAttribute(mega_kernel, cudaFuncAttributeMaxDynamicSharedMemorySize, SMEM_BYTES);
        cached[0] = w_gate; cached[1] = w_up; cached[2] = w_down; cached[3] = A_q; cached[4] = A_k; cached[5] = A_v;
        init = true;
    }
    mega_kernel<<<128, 512, SMEM_BYTES, cudaStreamPerThread>>>(A_q, A_k, A_v, A_shift, A_ssmk, A_ssmD, w_gate, w_up, w_down, (bf16*)d_out,
                                                               map_g, map_u, map_g32, map_u32, map_d, map_d32, map_k, map_kh, map_v, map_x);
}
```
